```python
import torch

def _softmax(x, axis=-1):
    return torch.softmax(x, dim=axis)
def _gelu(x):
    return torch.nn.functional.gelu(x, approximate="tanh")
def _silu(x):
    return torch.nn.functional.silu(x)
def _sigmoid(x):
    return torch.sigmoid(x)
def _layernorm(x, axis=-1, eps=1e-5):
    m = x.mean(dim=axis, keepdim=True)
    v = x.var(dim=axis, keepdim=True, unbiased=False)
    return (x - m) / torch.sqrt(v + eps)
def _scatter_add(tgt, idx, src, axis=0):
    return tgt.clone().index_add_(axis, idx, src)
def _segment_sum(src, seg, n):
    out = torch.zeros((n,) + src.shape[1:], dtype=src.dtype)
    return out.index_add_(0, seg, src)
def _pad(x, pw):
    flat = tuple(v for pair in reversed(pw) for v in pair)
    return torch.nn.functional.pad(x, flat)

kernel_name = 'standalone__molecular_angular_gemnet__graph'

def setup_inputs():

    _w = (lambda a: (lambda t: t.to(torch.bfloat16) if t.is_floating_point() else t)(torch.as_tensor(a)))
    N, deg, De, L = 10000, 16, 16, 1
    E = N * deg
    T = E * deg
    NR = 8
    dist = torch.rand(E).to(float)
    angle = (torch.rand(T) * torch.pi).to(float)
    centers = torch.linspace(0.0, 1.0, NR).to(float)
    ang_freq = torch.arange(1, L + 1).to(float)
    return {
        "m": _w((lambda *s: torch.randn(*s, dtype=torch.bfloat16) * 0.05)(E, De)),
        "idx_in": _w((lambda lo, hi, *s: torch.randint(lo, hi, s))(0, E, T).to(torch.int64)),
        "idx_out": _w((lambda lo, hi, *s: torch.randint(lo, hi, s))(0, E, T).to(torch.int64)),
        "dist": _w(dist),
        "angle": _w(angle),
        "centers": _w(centers),
        "ang_freq": _w(ang_freq),
        "w_rbf": _w((lambda *s: torch.randn(*s, dtype=torch.bfloat16) * 0.2)(NR, De)),
        "w_sbf": _w((lambda *s: torch.randn(*s, dtype=torch.bfloat16) * 0.2)(NR * L, De)),
        "w_down": _w((lambda *s: torch.randn(*s, dtype=torch.bfloat16) * 0.2)(De, De)),
        "w_up": _w((lambda *s: torch.randn(*s, dtype=torch.bfloat16) * 0.2)(De, De)),
    }

def reference(m, idx_in, idx_out, dist, angle, centers, ang_freq, w_rbf, w_sbf, w_down, w_up):
    E, De = m.shape[0], m.shape[1]
    NR = centers.shape[0]
    L = ang_freq.shape[0]
    rbf = torch.exp(-10.0 * (dist[:, None] - centers[None, :]) ** 2)
    cbf = torch.cos(ang_freq[None, :] * angle[:, None])
    rbf_t = rbf[idx_out]
    sbf = torch.reshape(rbf_t[:, :, None] * cbf[:, None, :], (-1, NR * L))
    x = (m[idx_in] @ w_down) * (sbf @ w_sbf)
    agg = _segment_sum(x, idx_out, E)
    return m + (agg @ w_up) * (rbf @ w_rbf)
```

```cpp
#include <cuda.h>
#include <cuda_runtime.h>
#include <cuda_bf16.h>
#include <stdint.h>

namespace {

constexpr int E_ = 160000;
constexpr int T_ = 2560000;
constexpr int NTILE = E_ / 16;
constexpr int NB = 132;
constexpr int TPB = 76;
constexpr int ROWS_PB = TPB * 16;
constexpr int NQUAD = T_ / 4;

constexpr int NGW = 19, NFW = 11;
constexpr int NW = NGW + NFW + 2;
constexpr int W_F0 = NGW + 1;
constexpr int TPW = TPB / NGW;
constexpr int NTHREADS = NW * 32;
constexpr int FT = NFW * 32;
constexpr int RPW = NB / NFW;
static_assert(RPW * NFW == NB, "");

#define R0Q_ 896
#define RQ_ 992
#define SFIRST 0
#define PFIRST 1
#define LEAD_ 3
constexpr int R0Q = R0Q_, RQ = RQ_;
constexpr int NROUND = 1 + ((NQUAD / 16 / NB + 1) * 16 - R0Q + RQ - 1) / RQ;
static_assert(R0Q % 32 == 0 && RQ % 32 == 0 && R0Q <= RQ && RQ <= (NW - 1) * 32, "rounds 0 and 1: one quad per thread");
static_assert(RQ <= 3 * FT && NQUAD / 16 / NB * 16 - R0Q - (NROUND - 2) * RQ >= 2 * FT,
              "front-end rounds take two full passes and a partial one");
__device__ __forceinline__ int round_start(int r) { return R0Q + (r - 1) * RQ; }
#define RALT_ (NROUND - 2)
constexpr int RALT = RALT_;

constexpr int BLK = 39, NOV = 64;
constexpr int CAP2 = 96;
constexpr int TS = CAP2 + 4;
constexpr int TCN = TPB + 32;
constexpr int PCN = NB + 4;
constexpr size_t SLAB = (size_t)NB * NB * 256;

constexpr int TB_ROWS = TPB * TS * 4;
constexpr int TB_SIZE = (TPB * TS * 5 + 127) / 128 * 128;
constexpr int SM_TB = 0;
constexpr int SM_IN0 = SM_TB;
constexpr int SM_PB1 = SM_TB + TB_SIZE;
constexpr int PB_OV = (NB + 1) * 256;
constexpr int SM_PB = SM_TB + 2 * TB_SIZE;
constexpr int SM_IN = SM_PB + PB_OV + NOV * 8;
constexpr int SM_RUN = SM_IN + RQ * 40;
constexpr int SM_RA = SM_PB;
constexpr int SM_ACC = SM_RA + TPB * 256;
constexpr int SM_PCNT = SM_RUN + NB * 256;
constexpr int SM_TCNT = SM_PCNT + 2 * PCN * 4;
constexpr int SM_WF = SM_TCNT + 2 * TCN * 4;
constexpr int SM_BAR = SM_WF + 12 * 32 * 4;
constexpr int SM_FLAG = SM_BAR + (10 + 5 * NROUND) * 8;
constexpr int SM_FREQ = SM_FLAG + 4;
constexpr int SM_TOTAL = SM_FLAG + 16;
static_assert(R0Q * 40 <= TB_SIZE && NB * 256 + 256 <= RQ * 40 && RALT >= 1 && PB_OV + NOV * 8 <= TB_SIZE && SM_RUN % 128 == 0 && SM_BAR % 8 == 0, "layout");
static_assert(SM_ACC + TPB * 1024 <= SM_PCNT, "epilogue scratch");
static_assert(SM_TOTAL <= 195 * 1024, "stay within the 196 KB carve-out: the gathers need the rest as L1");
constexpr int B_TFULL = SM_BAR, B_TFREE = SM_BAR + 16, B_DONE = SM_BAR + 32,
              B_PFULL = SM_BAR + 80, B_PFREE = B_PFULL + 8 * NROUND,
              B_RFULL = B_PFREE + 8 * NROUND, B_RFREE = B_RFULL + 8 * NROUND, B_IN = B_RFREE + 8 * NROUND;

struct Params {
    CUtensorMap blocks;
    cudaTextureObject_t tex;
    const uint16_t *m, *dist, *angle, *centers, *ang_freq, *w_rbf, *w_sbf, *w_down, *w_up;
    const int *idx_in, *idx_out;
    uint16_t* out;
    unsigned char* rec;
    unsigned* cnt;
};

__device__ __align__(256) uint4 g_rec[(NROUND * SLAB + NROUND * NB * NOV * 8) / 16];
__device__ unsigned g_cnt[(NROUND + 1) * 32];

#define TL(slot) do {} while (0)

__device__ __forceinline__ void mbar_init(uint32_t a, uint32_t n) {
    asm volatile("mbarrier.init.shared::cta.b64 [%0], %1;" ::"r"(a), "r"(n) : "memory");
}
__device__ __forceinline__ void mbar_arrive(uint32_t a) {
    asm volatile("mbarrier.arrive.shared::cta.b64 _, [%0];" ::"r"(a) : "memory");
}
template <int SLEEP>
__device__ __forceinline__ void mbar_wait(uint32_t a, uint32_t parity) {
#pragma unroll 1
    for (int it = 0; it < (1 << 14); it++) {
        uint32_t ok;
        asm volatile("{.reg .pred p; mbarrier.try_wait.parity.shared::cta.b64 p, [%1], %2; selp.u32 %0, 1, 0, p;}"
                     : "=r"(ok) : "r"(a), "r"(parity) : "memory");
        if (ok) break;
        __nanosleep(SLEEP);
    }
}
__device__ __forceinline__ bool mbar_done(uint32_t a, uint32_t parity) {
    uint32_t ok;
    asm volatile("{.reg .pred p; mbarrier.test_wait.parity.shared::cta.b64 p, [%1], %2; selp.u32 %0, 1, 0, p;}"
                 : "=r"(ok) : "r"(a), "r"(parity) : "memory");
    return ok;
}
template <int ID, int N> __device__ __forceinline__ void bar_sync() {
    asm volatile("bar.sync %0, %1;" ::"n"(ID), "n"(N) : "memory");
}
__device__ __forceinline__ uint32_t lds32(uint32_t a) {
    uint32_t v; asm volatile("ld.shared.u32 %0, [%1];" : "=r"(v) : "r"(a) : "memory"); return v;
}
__device__ __forceinline__ uint32_t lds16(uint32_t a) {
    uint32_t v; asm volatile("ld.shared.u16 %0, [%1];" : "=r"(v) : "r"(a) : "memory"); return v;
}
__device__ __forceinline__ uint2 lds64(uint32_t a) {
    uint2 v; asm volatile("ld.shared.v2.u32 {%0,%1}, [%2];" : "=r"(v.x), "=r"(v.y) : "r"(a) : "memory"); return v;
}
__device__ __forceinline__ int4 lds128(uint32_t a) {
    int4 v;
    asm volatile("ld.shared.v4.u32 {%0,%1,%2,%3}, [%4];" : "=r"(v.x), "=r"(v.y), "=r"(v.z), "=r"(v.w) : "r"(a) : "memory");
    return v;
}
__device__ __forceinline__ void sts32(uint32_t a, uint32_t v) {
    asm volatile("st.shared.u32 [%0], %1;" ::"r"(a), "r"(v) : "memory");
}
__device__ __forceinline__ uint32_t claim(uint32_t cnt_addr) {
    uint32_t pos;
    asm volatile("atom.shared.add.u32 %0, [%1], 1;" : "=r"(pos) : "r"(cnt_addr) : "memory");
    return pos;
}
__device__ __forceinline__ void put16(bool ok, uint32_t aw, uint32_t w, uint32_t ah, uint32_t h16) {
    asm volatile("{.reg .pred p; .reg .b16 h; setp.ne.u32 p, %0, 0; cvt.u16.u32 h, %4;\n\t"
                 "@p st.shared.u32 [%1], %2; @p st.shared.u16 [%3], h;}"
                 ::"r"((uint32_t)ok), "r"(aw), "r"(w), "r"(ah), "r"(h16) : "memory");
}
__device__ __forceinline__ void put8(bool ok, uint32_t aw, uint32_t w, uint32_t ab, uint32_t b8) {
    asm volatile("{.reg .pred p; setp.ne.u32 p, %0, 0;\n\t"
                 "@p st.shared.u32 [%1], %2; @p st.shared.u8 [%3], %4;}"
                 ::"r"((uint32_t)ok), "r"(aw), "r"(w), "r"(ab), "r"(b8) : "memory");
}
__device__ __forceinline__ uint32_t beq2(uint32_t a, uint32_t b) {
    uint32_t d;
    asm("set.eq.bf16x2.bf16x2 %0, %1, %2;" : "=r"(d) : "r"(a), "r"(b));
    return d;
}
__device__ __forceinline__ uint32_t movm(uint32_t a) {
    uint32_t d;
    asm volatile("movmatrix.sync.aligned.m8n8.trans.b16 %0, %1;" : "=r"(d) : "r"(a));
    return d;
}
__device__ __forceinline__ void mma16816(float (&c)[4], uint32_t a0, uint32_t a1, uint32_t a2, uint32_t a3,
                                         uint32_t b0, uint32_t b1) {
    asm volatile("mma.sync.aligned.m16n8k16.row.col.f32.bf16.bf16.f32 {%0,%1,%2,%3}, {%4,%5,%6,%7}, {%8,%9}, {%0,%1,%2,%3};"
                 : "+f"(c[0]), "+f"(c[1]), "+f"(c[2]), "+f"(c[3])
                 : "r"(a0), "r"(a1), "r"(a2), "r"(a3), "r"(b0), "r"(b1));
}
__device__ __forceinline__ void mma1688(float (&c)[4], uint32_t a0, uint32_t a1, uint32_t b0) {
    asm volatile("mma.sync.aligned.m16n8k8.row.col.f32.bf16.bf16.f32 {%0,%1,%2,%3}, {%4,%5}, {%6}, {%0,%1,%2,%3};"
                 : "+f"(c[0]), "+f"(c[1]), "+f"(c[2]), "+f"(c[3])
                 : "r"(a0), "r"(a1), "r"(b0));
}
__device__ __forceinline__ uint32_t pack_bf16(float lo, float hi) {
    uint32_t d;
    asm("cvt.rn.bf16x2.f32 %0, %1, %2;" : "=r"(d) : "f"(hi), "f"(lo));
    return d;
}
__device__ __forceinline__ float bf_lo(uint32_t v) { return __uint_as_float(v << 16); }
__device__ __forceinline__ float bf_hi(uint32_t v) { return __uint_as_float(v & 0xffff0000u); }
__device__ __forceinline__ float rnd_bf(float x) { return bf_lo(pack_bf16(x, 0.f)); }
__device__ __forceinline__ uint32_t hmul2_bf(uint32_t a, uint32_t b) {
    uint32_t d;
    asm("mul.rn.bf16x2 %0, %1, %2;" : "=r"(d) : "r"(a), "r"(b));
    return d;
}
__device__ __forceinline__ uint32_t cos_pack2(uint32_t c) {
    const uint32_t big = ((c >> 13) & 0x00010001u) * 0x1FFFu;
    return (c & big) | ((c >> 2) & 0x20002000u);
}
__device__ __forceinline__ uint32_t hmul2_lo(uint32_t v, uint32_t k) {
    uint32_t d;
    asm("{.reg .b16 l, h; .reg .b32 t; mov.b32 {l, h}, %2; mov.b32 t, {l, l}; mul.rn.bf16x2 %0, %1, t;}"
        : "=r"(d) : "r"(v), "r"(k));
    return d;
}
__device__ __forceinline__ uint32_t hmul2_hi(uint32_t v, uint32_t k) {
    uint32_t d;
    asm("{.reg .b16 l, h; .reg .b32 t; mov.b32 {l, h}, %2; mov.b32 t, {h, h}; mul.rn.bf16x2 %0, %1, t;}"
        : "=r"(d) : "r"(v), "r"(k));
    return d;
}

struct Quad { int4 io, ii; uint2 an; };

template <int CAPQ>
__device__ __forceinline__ void stage_inputs(uint32_t dst, uint32_t bar, const Params& p, int q, int n) {
    uint64_t pol;
    asm volatile("createpolicy.fractional.L2::evict_first.b64 %0, 1.0;" : "=l"(pol));
    asm volatile("mbarrier.arrive.expect_tx.shared::cta.b64 _, [%0], %1;" ::"r"(bar), "r"(n * 40) : "memory");
    auto cp = [&](uint32_t d, const void* src, int bytes) {
        asm volatile("cp.async.bulk.shared::cluster.global.mbarrier::complete_tx::bytes.L2::cache_hint [%0], [%1], %2, [%3], %4;"
                     ::"r"(d), "l"(src), "r"(bytes), "r"(bar), "l"(pol) : "memory");
    };
    cp(dst, p.idx_out + 4 * (size_t)q, n * 16);
    cp(dst + CAPQ * 16, p.idx_in + 4 * (size_t)q, n * 16);
    cp(dst + CAPQ * 32, p.angle + 4 * (size_t)q, n * 8);
}

template <int N>
__device__ __forceinline__ void p_quads(uint32_t pb, uint32_t pc, const Quad (&v)[N], uint32_t fr2) {
    uint32_t x[N][2], io[N][4], bin[N][4], pos[N][4], w[N][4];
#pragma unroll
    for (int n = 0; n < N; n++) {
        x[n][0] = hmul2_bf(v[n].an.x, fr2);
        x[n][1] = hmul2_bf(v[n].an.y, fr2);
        const bool big = (((x[n][0] & 0x7FFF7FFFu) + 0x3D003D00u) | ((x[n][1] & 0x7FFF7FFFu) + 0x3D003D00u)) & 0x80008000u;
        const uint32_t inc = big ? 0x10001u : 1u;
        io[n][0] = v[n].io.x; io[n][1] = v[n].io.y; io[n][2] = v[n].io.z; io[n][3] = v[n].io.w;
#pragma unroll
        for (int i = 0; i < 4; i++) {
            bin[n][i] = __umulhi(io[n][i], 3532046u);
            asm volatile("atom.shared.add.u32 %0, [%1], %2;" : "=r"(pos[n][i])
                         : "r"(pc + bin[n][i] * 4), "r"(inc) : "memory");
        }
    }
    uint32_t top = 0;
#pragma unroll
    for (int n = 0; n < N; n++) {
        const uint32_t c01 = cos_pack2(pack_bf16(__cosf(bf_lo(x[n][0])), __cosf(bf_hi(x[n][0]))));
        const uint32_t c23 = cos_pack2(pack_bf16(__cosf(bf_lo(x[n][1])), __cosf(bf_hi(x[n][1]))));
        w[n][0] = (c01 << 18) | v[n].ii.x;
        w[n][1] = ((c01 << 2) & 0xFFFC0000u) | v[n].ii.y;
        w[n][2] = (c23 << 18) | v[n].ii.z;
        w[n][3] = ((c23 << 2) & 0xFFFC0000u) | v[n].ii.w;
#pragma unroll
        for (int i = 0; i < 4; i++) {
            const uint32_t base = pb + bin[n][i] * 256, k = pos[n][i];
            io[n][i] -= bin[n][i] * ROWS_PB;
            const uint32_t sl = (bin[n][i] * 6 + k) & 31;
            const uint32_t aw = k < 32 ? base + sl * 4 : base + k * 8 - 56;
            put16(k < BLK, aw, w[n][i], k < 32 ? base + 136 + sl * 2 : aw + 4, io[n][i]);
            top = max(top, k);
        }
    }
    if (top >= BLK) {
#pragma unroll
        for (int n = 0; n < N; n++)
#pragma unroll
            for (int i = 0; i < 4; i++)
                if (pos[n][i] >= BLK && bin[n][i] < NB) {
                    const uint32_t k = claim(pc + (NB + 1) * 4);
                    if (k < NOV)
                        asm volatile("st.shared.v2.u32 [%0], {%1,%2};" ::"r"(pb + PB_OV + k * 8), "r"(w[n][i]),
                                     "r"(bin[n][i] << 16 | io[n][i]) : "memory");
                    else
                        asm volatile("red.shared.add.u32 [%0], 0x10000;" ::"r"(pc + bin[n][i] * 4) : "memory");
                }
    }
}

template <int CAPQ>
__device__ __forceinline__ Quad staged_quad(uint32_t in, int i) {
    Quad c;
    c.io = lds128(in + i * 16);
    c.ii = lds128(in + CAPQ * 16 + i * 16);
    c.an = lds64(in + CAPQ * 32 + i * 8);
    return c;
}

__device__ __forceinline__ void publish(unsigned* cnt, int r) {
    asm volatile("red.release.gpu.global.add.u32 [%0], 1;" ::"l"(cnt + r * 32) : "memory");
}
__device__ __forceinline__ bool wait_round(const unsigned* cnt, int r) {
    unsigned c;
    int spins = 0;
    do {
        asm volatile("ld.relaxed.gpu.global.u32 %0, [%1];" : "=r"(c) : "l"(cnt + r * 32) : "memory");
    } while (c < NB && ++spins < (1 << 14));
    asm volatile("ld.acquire.gpu.global.u32 %0, [%1];" : "=r"(c) : "l"(cnt + r * 32) : "memory");
    return c >= NB;
}
__device__ __forceinline__ void fetch_runs(uint32_t sb, bool ok, uint32_t dst, const unsigned char* src, int bytes, uint32_t bar) {
    if (ok) {
        asm volatile("fence.proxy.async.global;" ::: "memory");
        asm volatile("mbarrier.arrive.expect_tx.shared::cta.b64 _, [%0], %1;" ::"r"(bar), "r"(bytes) : "memory");
        uint64_t pol;
        asm volatile("createpolicy.fractional.L2::evict_first.b64 %0, 1.0;" : "=l"(pol));
        asm volatile("cp.async.bulk.shared::cluster.global.mbarrier::complete_tx::bytes.L2::cache_hint [%0], [%1], %2, [%3], %4;"
                     ::"r"(dst), "l"(src), "r"(bytes), "r"(bar), "l"(pol) : "memory");
    } else {
        sts32(sb + SM_FLAG, 2);
        mbar_arrive(bar);
    }
}

__device__ __forceinline__ int run_buffer(int r) { return r >= RALT && ((r - RALT) & 1) == 0 ? SM_IN : SM_RUN; }

struct Sorter {
    uint32_t cb, wb, rb, none;
    uint32_t least = 0xFFFFFFFFu;
    __device__ __forceinline__ Sorter(uint32_t sb, uint32_t buf, int lane) {
        cb = sb + SM_TCNT + buf * TCN * 4;
        wb = sb + SM_TB + buf * TB_SIZE;
        rb = wb + TB_ROWS;
        none = (TPB + lane) << 4;
    }
    __device__ __forceinline__ uint32_t checked(uint32_t n, uint32_t cap) {
        if (n > cap) least = 0;
        return n > cap ? 0 : n;
    }
    __device__ __forceinline__ uint32_t slot(uint32_t loc) const { return claim(cb + (loc >> 4) * 4); }
    __device__ __forceinline__ void store(uint32_t w, uint32_t loc, uint32_t pos) {
        const uint32_t e = (loc >> 4) * TS + pos;
        put8(pos < CAP2, wb + e * 4, w, rb + e, loc & 15);
        least = min(least, pos - CAP2);
    }
    __device__ __forceinline__ void listed(const unsigned char* list, uint32_t bin, int lane) {
        uint2 e[NOV / 32];
#pragma unroll
        for (int i = 0; i < NOV / 32; i++)
            asm volatile("ld.relaxed.gpu.global.v2.u32 {%0,%1}, [%2];" : "=r"(e[i].x), "=r"(e[i].y)
                         : "l"(list + (i * 32 + lane) * 8) : "memory");
#pragma unroll
        for (int i = 0; i < NOV / 32; i++)
            if (e[i].y >> 16 == bin) store(e[i].x, e[i].y & 0xFFFFu, slot(e[i].y & 0xFFFFu));
    }
    __device__ __forceinline__ bool overflow() const { return least < 0x20000000u; }
};

template <int N>
__device__ __forceinline__ bool s_round(uint32_t sb, const unsigned char* rec, int r, int cta, int p0, int lane) {
    Sorter s(sb, r & 1, lane);
    const uint32_t run = sb + run_buffer(r) + p0 * 256;
    const uint32_t rk = (lane - cta * 6) & 31;
    const uint32_t sub = lane >> 3, tk = (lane & 7) == 7 ? 1000 : 32 + (lane & 7);
    uint32_t more = 0;
#pragma unroll
    for (int u0 = 0; u0 < N; u0 += 4) {
        uint32_t w[5], loc[5], pos[5], n[4];
#pragma unroll
        for (int u = 0; u < 4; u++) {
            const bool on = u0 + u < N && (NB % N == 0 || p0 + u0 + u < NB);
            n[u] = on ? lds32(run + (u0 + u) * 256 + 128) : 0u;
            if (u0 + u < N) {
                loc[u] = lds16(run + (u0 + u) * 256 + 136 + lane * 2);
                w[u] = lds32(run + (u0 + u) * 256 + lane * 4);
            }
        }
        const uint2 e = lds64(run + u0 * 256 + sub * 256 + 200 + (lane & 7) * 8 - ((lane & 7) == 7 ? 8 : 0));
#pragma unroll
        for (int u = 0; u < 4; u++) {
            n[u] = s.checked(n[u], BLK + NOV);
            if (u0 + u < N) {
                if (rk >= n[u]) loc[u] = s.none;
                pos[u] = s.slot(loc[u]);
                if (n[u] > BLK) more |= 1u << (u0 + u);
            }
        }
        w[4] = e.x;
        loc[4] = tk < (sub == 0 ? n[0] : sub == 1 ? n[1] : sub == 2 ? n[2] : n[3]) ? e.y & 0xFFFFu : s.none;
        pos[4] = s.slot(loc[4]);
#pragma unroll
        for (int u = 0; u < 5; u++)
            if (u == 4 || u0 + u < N) s.store(w[u], loc[u], pos[u]);
    }
    for (; more; more &= more - 1)
        s.listed(rec + NROUND * SLAB + (size_t)(r * NB + p0 + __ffs(more) - 1) * (NOV * 8), cta, lane);
    return s.overflow();
}

__device__ __forceinline__ uint2 rbf_tile(int tile, int lane, const Params& p) {
    const int r0 = tile * 16 + (lane >> 2);
    const uint32_t d0 = __ldg(p.dist + r0) * 0x10001u, d1 = __ldg(p.dist + r0 + 8) * 0x10001u;
    const uint32_t cc = __ldg(reinterpret_cast<const uint32_t*>(p.centers) + (lane & 3));
    auto rbf = [&](uint32_t d) {
        uint32_t t;
        asm("sub.rn.bf16x2 %0, %1, %2;" : "=r"(t) : "r"(d), "r"(cc));
        t = hmul2_bf(hmul2_bf(t, t), 0xC120C120u);
        return pack_bf16(__expf(bf_lo(t)), __expf(bf_hi(t)));
    };
    return make_uint2(rbf(d0), rbf(d1));
}

struct Weights {
    uint32_t v[12];
    __device__ __forceinline__ Weights(uint32_t sb, int lane) {
#pragma unroll
        for (int i = 0; i < 12; i++) v[i] = lds32(sb + SM_WF + i * 128 + lane * 4);
    }
};
struct MRows {
    uint2 a, b;
    __device__ __forceinline__ MRows(int tile, int lane, const Params& p) {
        const uint2* m2 = reinterpret_cast<const uint2*>(p.m) + (tile * 16 + (lane >> 2)) * 4 + (lane & 3);
        a = __ldg(m2);
        b = __ldg(m2 + 32);
    }
};

__device__ __forceinline__ void epilogue(const float (&s0)[4], const float (&s1)[4], uint2 ra, const MRows& mr,
                                         const Weights& w, int tile, int lane, uint16_t* out) {
    uint32_t h[4], l[4];
    h[0] = pack_bf16(s0[0], s0[1]); h[1] = pack_bf16(s0[2], s0[3]);
    h[2] = pack_bf16(s1[0], s1[1]); h[3] = pack_bf16(s1[2], s1[3]);
    l[0] = pack_bf16(s0[0] - bf_lo(h[0]), s0[1] - bf_hi(h[0]));
    l[1] = pack_bf16(s0[2] - bf_lo(h[1]), s0[3] - bf_hi(h[1]));
    l[2] = pack_bf16(s1[0] - bf_lo(h[2]), s1[1] - bf_hi(h[2]));
    l[3] = pack_bf16(s1[2] - bf_lo(h[3]), s1[3] - bf_hi(h[3]));
    uint32_t a[4];
#pragma unroll
    for (int n = 0; n < 2; n++) {
        float y[4] = {}, gs[4] = {};
        mma16816(y, l[0], l[1], l[2], l[3], w.v[2 * n], w.v[2 * n + 1]);
        mma16816(y, h[0], h[1], h[2], h[3], w.v[2 * n], w.v[2 * n + 1]);
        mma1688(gs, ra.x, ra.y, w.v[8 + n]);
        a[2 * n] = pack_bf16(y[0] * gs[0], y[1] * gs[1]);
        a[2 * n + 1] = pack_bf16(y[2] * gs[2], y[3] * gs[3]);
    }
    const uint32_t mm[4] = {mr.a.x, mr.b.x, mr.a.y, mr.b.y};
    uint32_t o[4];
#pragma unroll
    for (int n = 0; n < 2; n++) {
        float u[4] = {}, hr[4] = {};
        mma16816(u, a[0], a[1], a[2], a[3], w.v[4 + 2 * n], w.v[5 + 2 * n]);
        mma1688(hr, ra.x, ra.y, w.v[10 + n]);
#pragma unroll
        for (int k = 0; k < 2; k++) {
            const uint32_t t = hmul2_bf(pack_bf16(u[2 * k], u[2 * k + 1]), pack_bf16(hr[2 * k], hr[2 * k + 1]));
            asm("add.rn.bf16x2 %0, %1, %2;" : "=r"(o[2 * n + k]) : "r"(mm[2 * n + k]), "r"(t));
        }
    }
    uint2* out2 = reinterpret_cast<uint2*>(out) + (tile * 16 + (lane >> 2)) * 4 + (lane & 3);
    out2[0] = make_uint2(o[0], o[2]);
    out2[32] = make_uint2(o[1], o[3]);
}

__device__ __forceinline__ void load_acc(uint32_t sb, int lt, int lane, float (&s0)[4], float (&s1)[4]) {
#pragma unroll
    for (int i = 0; i < 4; i++) {
        s0[i] = __uint_as_float(lds32(sb + SM_ACC + lt * 1024 + i * 128 + lane * 4));
        s1[i] = __uint_as_float(lds32(sb + SM_ACC + lt * 1024 + (4 + i) * 128 + lane * 4));
    }
}

__device__ __forceinline__ uint32_t and_or(uint32_t a, uint32_t m, uint32_t c) {
    uint32_t d;
    asm("lop3.b32 %0, %1, %2, %3, 0xEA;" : "=r"(d) : "r"(a), "r"(m), "r"(c));
    return d;
}

struct Group {
    uint2 v0, v1;
    uint32_t k, rows;
    __device__ __forceinline__ void issue(uint32_t aw, uint32_t ar, cudaTextureObject_t tex, uint32_t q) {
        const uint2 w = lds64(aw);
        rows = lds32(ar);
        v0 = tex1Dfetch<uint2>(tex, (int)and_or(w.x << 2, 0xFFFFCu, q));
        v1 = tex1Dfetch<uint2>(tex, (int)and_or(w.y << 2, 0xFFFFCu, q));
        k = __byte_perm(w.x, w.y, 0x7632);
    }
    __device__ __forceinline__ void consume(float (&c0)[4], float (&c1)[4], uint32_t gg, uint32_t gg8) const {
        const uint32_t ra = __byte_perm(rows, 0, 0x2404), rc = __byte_perm(rows, 0, 0x3414);
        const uint32_t a0 = beq2(ra, gg), a1 = beq2(ra, gg8);
        const uint32_t a2 = beq2(rc, gg), a3 = beq2(rc, gg8);
        const uint32_t c = ((k >> 2) & 0x1FFF1FFFu) | (k & 0x80008000u) | 0x20002000u;
        const uint32_t b0 = movm(hmul2_lo(v0.x, c)), b1 = movm(hmul2_hi(v1.x, c));
        const uint32_t b2 = movm(hmul2_lo(v0.y, c)), b3 = movm(hmul2_hi(v1.y, c));
        mma16816(c0, a0, a1, a2, a3, b0, b1);
        mma16816(c1, a0, a1, a2, a3, b2, b3);
    }
};

#define GD_ 2
constexpr int GD = GD_;

__device__ __forceinline__ void slow_path(uint32_t sb, float* acc, const Params& p) {
    const int tid = threadIdx.x;
    for (int i = tid; i < TPB * 256; i += NTHREADS) acc[i] = 0.f;
    __syncthreads();
    const uint32_t fr2 = lds32(sb + SM_FREQ);
    for (int t = tid; t < T_; t += NTHREADS) {
        const uint32_t lo = (uint32_t)(p.idx_out[t] - (int)blockIdx.x * ROWS_PB);
        if (lo < (uint32_t)ROWS_PB) {
            const float c = rnd_bf(cosf(bf_lo(hmul2_bf(p.angle[t], fr2))));
            const uint32_t* row = reinterpret_cast<const uint32_t*>(p.m) + (size_t)p.idx_in[t] * 8;
            float* a = acc + (lo >> 4) * 256 + (lo & 8) * 8 + (lo & 7) * 4;
#pragma unroll
            for (int i = 0; i < 8; i++) {
                const uint32_t x = row[i];
                atomicAdd(a + (i & 1) * 128 + (i >> 1), c * bf_lo(x));
                atomicAdd(a + (i & 1) * 128 + (i >> 1) + 32, c * bf_hi(x));
            }
        }
    }
    __syncthreads();
    for (int lt = tid >> 5; lt < TPB && blockIdx.x * TPB + lt < NTILE; lt += NW) {
        const int tile = blockIdx.x * TPB + lt, lane = tid & 31;
        float s0[4], s1[4];
        load_acc(sb, lt, lane, s0, s1);
        epilogue(s0, s1, rbf_tile(tile, lane, p), MRows(tile, lane, p), Weights(sb, lane), tile, lane, p.out);
    }
}

__device__ __forceinline__ void front_end(uint32_t sb, const Params& p, int cta, int fw, int lane) {
    const int ft = fw * 32 + lane;
    const int nq_all = (cta + 1) * (NQUAD / 16) / NB * 16 - cta * (NQUAD / 16) / NB * 16;
    for (int k = fw; k < 12; k += NFW) {
        const int g = lane >> 2, q = lane & 3;
        const int n = k < 8 ? (k >> 1) & 1 : k & 1;
        const int row = k < 8 ? 4 * q + 2 * (k & 1) : 2 * q;
        const uint16_t* w = (k < 4 ? p.w_down : k < 8 ? p.w_up : k < 10 ? p.w_sbf : p.w_rbf) +
                            row * 16 + 4 * (g >> 1) + 2 * n + (g & 1);
        sts32(sb + SM_WF + (k * 32 + lane) * 4, (uint32_t)w[0] | ((uint32_t)w[16] << 16));
    }
    const uint32_t fr2 = lds32(sb + SM_FREQ);
    int np = 2, r = 1;
#pragma unroll 1
    for (int idle = 0; r < NROUND;) {
        const bool late = idle > (1 << 18);
        const bool p_ready = np < NROUND && np <= r + LEAD_ && mbar_done(sb + B_PFREE + 8 * (np == 2 ? 0 : np - 1), 0) &&
                             mbar_done(sb + B_IN + 8 * np, 0);
        if (late || (!(PFIRST && p_ready) && mbar_done(sb + B_RFULL + 8 * r, 0) &&
                     (r < 2 || mbar_done(sb + B_TFREE + 8 * (r & 1), ((r >> 1) - 1) & 1)) && (SFIRST || r < NROUND - 1 || np > NROUND))) {
            if (fw == 1) TL(56 + r);
            if (lds32(sb + SM_FLAG) != 2 && s_round<RPW>(sb, p.rec, r, cta, fw * RPW, lane)) sts32(sb + SM_FLAG, 1);
            __syncwarp();
            if (lane == 0) {
                mbar_arrive(sb + B_TFULL + 8 * (r & 1));
                mbar_arrive(sb + B_RFREE + 8 * r);
            }
            if (fw == 1) TL(40 + r);
            r++;
        } else if (p_ready) {
            const int nq = min(round_start(np + 1), nq_all) - round_start(np);
            if (fw == 1) TL(3 + np);
            {
                const Quad c[2] = {staged_quad<RQ>(sb + SM_IN, ft), staged_quad<RQ>(sb + SM_IN, FT + ft)};
                p_quads<2>(sb + SM_PB, sb + SM_PCNT, c, fr2);
            }
            if (2 * FT + fw * 32 < nq) {
                Quad c[1] = {staged_quad<RQ>(sb + SM_IN, 2 * FT + ft)};
                if (2 * FT + ft >= nq) {
                    c[0].io = make_int4(NB * ROWS_PB, NB * ROWS_PB, NB * ROWS_PB, NB * ROWS_PB);
                    c[0].an = make_uint2(0, 0);
                }
                p_quads<1>(sb + SM_PB, sb + SM_PCNT, c, fr2);
            }
            asm volatile("fence.proxy.async.shared::cta;" ::: "memory");
            __syncwarp();
            if (lane == 0) mbar_arrive(sb + B_PFULL + 8 * np);
            if (fw == 1) TL(24 + np);
            np++;
        } else if (np == NROUND && mbar_done(sb + B_PFREE + 8 * (NROUND - 1), 0)) {
#pragma unroll 1
            for (int k0 = 0; k0 < 8; k0 += 4) {
#pragma unroll
                for (int k = k0; k < k0 + 4; k++) {
                    const int lt = min(fw + k * NFW, min(TPB, NTILE - cta * TPB) - 1);
                    const uint2 ra = rbf_tile(cta * TPB + lt, lane, p);
                    asm volatile("st.shared.v2.u32 [%0], {%1,%2};" ::"r"(sb + SM_RA + lt * 256 + lane * 8), "r"(ra.x), "r"(ra.y) : "memory");
                }
            }
            np++;
        } else {
            idle++;
            __nanosleep(100);
        }
    }
    bar_sync<2, FT>();
    if (lds32(sb + SM_FLAG) != 0) return;
    const Weights w(sb, lane);
#pragma unroll 1
    for (int lt = fw; lt < (TPW - 1) * NGW && cta * TPB + lt < NTILE; lt += NFW) {
        const int tile = cta * TPB + lt;
        const MRows mr(tile, lane, p);
        const uint2 ra = lds64(sb + SM_RA + lt * 256 + lane * 8);
        mbar_wait<100>(sb + B_DONE + 8 * (lt / NGW), 0);
        float s0[4], s1[4];
        load_acc(sb, lt, lane, s0, s1);
        epilogue(s0, s1, ra, mr, w, tile, lane, p.out);
    }
}

__device__ __forceinline__ void gather_role(uint32_t sb, const Params& p, int warp, int lane) {
    const int g = lane >> 2, q = lane & 3;
    const cudaTextureObject_t tex = p.tex;
    float acc[TPW][2][4];
#pragma unroll
    for (int j = 0; j < TPW; j++)
#pragma unroll
        for (int n = 0; n < 2; n++)
#pragma unroll
            for (int i = 0; i < 4; i++) acc[j][n][i] = 0.f;
    const uint32_t gg = g * 0x01000100u, gg8 = gg + 0x08000800u;
    uint32_t qo = q;
    asm volatile("" : "+r"(qo));
    static_assert(TPW == 4, "eight lanes per tile");
#pragma unroll 1
    for (int r = 0; r < NROUND; r++) {
        const int buf = r & 1;
        if (r > 0) mbar_wait<200>(sb + B_TFULL + 8 * buf, ((r - 1) >> 1) & 1);
        if (warp == 0) TL(10 + r);
        const uint32_t tb = sb + SM_TB + buf * TB_SIZE;
        const uint32_t aw = tb + warp * (TS * 4) + g * 8, ar = tb + TB_ROWS + warp * TS + q * 4;
        const uint32_t sj = warp + (lane >> 3) * NGW;
        const uint32_t cj = sb + SM_TCNT + (sj + buf * TCN) * 4;
        const uint32_t n = min(lds32(cj), (uint32_t)CAP2), np = (n + 15) & ~15u;
        const uint32_t e = n + (lane & 7);
        if (e < np) sts32(tb + (sj * TS + e) * 4, 0x3FFFFu);
        if (e + 8 < np) sts32(tb + (sj * TS + e + 8) * 4, 0x3FFFFu);
        __syncwarp();
        if ((lane & 7) == 0) sts32(cj, 0);
        const uint32_t act = __reduce_add_sync(0xffffffffu, (lane & 7) == 0 ? ((1u << (np >> 4)) - 1) << lane : 0u);
        const bool hand = r == NROUND - 1 && lds32(sb + SM_FLAG) == 0;
        auto hand_over = [&](int j, const float (&c)[2][4]) {
            const uint32_t d = sb + SM_ACC + (j * NGW + warp) * 1024 + lane * 4;
#pragma unroll
            for (int i = 0; i < 8; i++) sts32(d + i * 128, __float_as_uint(c[i >> 2][i & 3]));
            __syncwarp();
            if (lane == 0) mbar_arrive(sb + B_DONE + 8 * j);
        };
        Group x[GD];
        if (act & 0xF0F0F0F0u) {
#pragma unroll
            for (int j = 0; j < TPW; j++) {
#pragma unroll 1
                for (int k = 4; act >> (8 * j + k) & 1; k++) {
                    const int o = j * NGW * TS + k * 16;
                    x[0].issue(aw + o * 4, ar + o, tex, qo);
                    x[0].consume(acc[j][0], acc[j][1], gg, gg8);
                }
            }
        }
#pragma unroll
        for (int s = -GD; s < 4 * TPW; s++) {
            if (s >= 0 && (act >> (8 * (s >> 2) + (s & 3)) & 1)) x[s % GD].consume(acc[s >> 2][0], acc[s >> 2][1], gg, gg8);
            const int t = s + GD;
            if (t < 4 * TPW) {
                const int o = (t >> 2) * NGW * TS + (t & 3) * 16;
                x[t % GD].issue(aw + o * 4, ar + o, tex, (act >> (8 * (t >> 2) + (t & 3)) & 1) ? qo : 0x400000u);
            }
            if (s >= 0 && (s & 3) == 3 && s < 4 * (TPW - 1) && hand) hand_over(s >> 2, acc[s >> 2]);
        }
        __syncwarp();
        if (lane == 0) mbar_arrive(sb + B_TFREE + 8 * buf);
        if (warp == 0) TL(17 + r);
    }
    const int tile = blockIdx.x * TPB + (TPW - 1) * NGW + warp;
    if (lds32(sb + SM_FLAG) == 0 && tile < NTILE) {
        const MRows mr(tile, lane, p);
        epilogue(acc[TPW - 1][0], acc[TPW - 1][1], lds64(sb + SM_RA + ((TPW - 1) * NGW + warp) * 256 + lane * 8), mr,
                 Weights(sb, lane), tile, lane, p.out);
    }
}

#define PFK 1
#define PFS 37
#define WHEN_R1 1
#define WHEN_PF 1
__device__ __forceinline__ void prefetch_m(const Params& p, int cta) {
#pragma unroll 1
    for (int k = 0; k < PFK; k++) {
        const int c = (cta + k * PFS) % NB;
        const int l0 = c * (E_ / 4) / NB, l1 = (c + 1) * (E_ / 4) / NB;
        asm volatile("cp.async.bulk.prefetch.L2.global [%0], %1;" ::"l"(p.m + (size_t)l0 * 64), "r"((l1 - l0) * 128) : "memory");
    }
}

__device__ __forceinline__ void finish(uint32_t sb, unsigned char* sm, const Params& p) {
    __syncthreads();
    if (lds32(sb + SM_FLAG) != 0) slow_path(sb, reinterpret_cast<float*>(sm + SM_ACC), p);
    if (threadIdx.x == 0) {
        TL(1);
        if (atomicAdd(p.cnt + NROUND * 32, 1u) == NB - 1)
            for (int r = 0; r <= NROUND; r++) p.cnt[r * 32] = 0;
    }
}

__global__ void __launch_bounds__(NTHREADS, 1) gemnet_kernel(const __grid_constant__ Params p) {
    extern __shared__ __align__(128) unsigned char sm[];
    const uint32_t sb = (uint32_t)__cvta_generic_to_shared(sm);
    const int tid = threadIdx.x, warp = tid >> 5, lane = tid & 31;
    const int cta = blockIdx.x;

    const int qs = cta * (NQUAD / 16) / NB * 16;
    if (tid == 0) {
        mbar_init(sb + B_IN, 1);
        mbar_init(sb + B_IN + 8, 1);
        asm volatile("fence.mbarrier_init.release.cluster;" ::: "memory");
        stage_inputs<R0Q>(sb + SM_IN0, sb + B_IN, p, qs, R0Q);
        if (WHEN_R1 == 0) stage_inputs<RQ>(sb + SM_IN, sb + B_IN + 8, p, qs + R0Q, RQ);
        if (WHEN_PF == 0) prefetch_m(p, cta);
    } else if (tid == 32) {
        sts32(sb + SM_FREQ, (uint32_t)__ldg(p.ang_freq) * 0x10001u);
    } else if (tid == 64) {
        mbar_init(sb + B_TFULL, NFW);
        mbar_init(sb + B_TFULL + 8, NFW);
        mbar_init(sb + B_TFREE, NGW);
        mbar_init(sb + B_TFREE + 8, NGW);
        for (int j = 0; j < TPW - 1; j++) mbar_init(sb + B_DONE + 8 * j, NGW);
        sts32(sb + SM_FLAG, 0);
    } else if (tid >= 96 && tid < 96 + NROUND) {
        const int r = tid - 96;
        mbar_init(sb + B_PFULL + 8 * r, r == 0 ? R0Q / 32 : r == 1 ? RQ / 32 : NFW);
        mbar_init(sb + B_PFREE + 8 * r, 1);
        mbar_init(sb + B_RFULL + 8 * r, 1);
        if (r >= 2) mbar_init(sb + B_IN + 8 * r, 1);
        mbar_init(sb + B_RFREE + 8 * r, r == 0 ? NGW : NFW);
        asm volatile("fence.mbarrier_init.release.cluster;" ::: "memory");
    }
    if (tid >= 256 && tid < 256 + 2 * PCN) sts32(sb + SM_PCNT + (tid - 256) * 4, 0);
    if (tid < 2 * TCN) sts32(sb + SM_TCNT + tid * 4, tid % TCN < TPB ? 0u : 0x40000000u);
    __syncthreads();
    if (warp == 0) TL(3);

    if (warp != NGW) {
        const int pt = warp < NGW ? tid : tid - 32;
        const uint32_t fr2 = lds32(sb + SM_FREQ);
        if (pt < R0Q) {
            mbar_wait<20>(sb + B_IN, 0);
            if (warp == 0) TL(23);
            const Quad c[1] = {staged_quad<R0Q>(sb + SM_IN0, pt)};
            p_quads<1>(sb + SM_PB, sb + SM_PCNT, c, fr2);
            asm volatile("fence.proxy.async.shared::cta;" ::: "memory");
            __syncwarp();
            if (lane == 0) mbar_arrive(sb + B_PFULL);
            if (warp == 0) TL(24);
        }
        if (pt < RQ) {
            mbar_wait<20>(sb + B_IN + 8, 0);
            if (warp == 0) TL(4);
            const Quad c[1] = {staged_quad<RQ>(sb + SM_IN, pt)};
            p_quads<1>(sb + SM_PB1, sb + SM_PCNT + PCN * 4, c, fr2);
            asm volatile("fence.proxy.async.shared::cta;" ::: "memory");
            __syncwarp();
            if (lane == 0) mbar_arrive(sb + B_PFULL + 8);
            if (warp == 0) TL(25);
        }
    }

    if (warp < W_F0) {
        if (warp == NGW) {
            const int nq_all = (cta + 1) * (NQUAD / 16) / NB * 16 - qs;
            if (lane == 0 && (WHEN_R1 == 1 || WHEN_PF == 1)) {
                mbar_wait<20>(sb + B_IN, 0);
                if (WHEN_R1 == 1) stage_inputs<RQ>(sb + SM_IN, sb + B_IN + 8, p, qs + R0Q, RQ);
                if (WHEN_PF == 1) prefetch_m(p, cta);
            }
#pragma unroll 1
            for (int r = 0; r < NROUND; r++) {
                const uint32_t pb = sb + (r == 1 ? SM_PB1 : SM_PB), pc = sb + SM_PCNT + (r == 1 ? PCN * 4 : 0);
                __syncwarp();
                mbar_wait<20>(sb + B_PFULL + 8 * r, 0);
                if (lane == 0 && r >= 1 && r + 1 < NROUND)
                    stage_inputs<RQ>(sb + SM_IN, sb + B_IN + 8 * (r + 1), p, qs + round_start(r + 1),
                                     min(round_start(r + 2), nq_all) - round_start(r + 1));
#pragma unroll
                for (int b = lane; b < NB; b += 32) {
                    sts32(pb + b * 256 + 128, lds32(pc + b * 4));
                    sts32(pc + b * 4, 0);
                }
                const uint32_t nov = lds32(pc + (NB + 1) * 4);
#pragma unroll
                for (uint32_t k = lane; k < NOV; k += 32)
                    if (k >= nov) sts32(pb + PB_OV + k * 8 + 4, 0xFFFF0000u);
                __syncwarp();
                if (lane == 0) sts32(pc + (NB + 1) * 4, 0);
                asm volatile("fence.proxy.async.shared::cta;" ::: "memory");
                __syncwarp();
                if (lane == 0) {
                    asm volatile("cp.async.bulk.tensor.3d.global.shared::cta.tile.bulk_group [%0, {%1, %2, %3}], [%4];"
                                 ::"l"(&p.blocks), "r"(0), "r"(cta), "r"(r * NB), "r"(pb) : "memory");
                    if (nov)
                        asm volatile("cp.async.bulk.global.shared::cta.bulk_group [%0], [%1], %2;"
                                     ::"l"(p.rec + NROUND * SLAB + (size_t)(r * NB + cta) * (NOV * 8)), "r"(pb + PB_OV),
                                       "n"(NOV * 8) : "memory");
                    asm volatile("cp.async.bulk.commit_group;" ::: "memory");
                    if (r == 0 && WHEN_PF == 2) prefetch_m(p, cta);
                    if (r == 1 && WHEN_PF == 3) prefetch_m(p, cta);
                    asm volatile("cp.async.bulk.wait_group.read 0;" ::: "memory");
                    mbar_arrive(sb + B_PFREE + 8 * r);
                    asm volatile("cp.async.bulk.wait_group 0;" ::: "memory");
                    publish(p.cnt, r);
                    TL(48 + r);
                }
            }
            __syncwarp();
        } else {
            mbar_wait<50>(sb + B_RFULL, 0);
            if (warp == 0) TL(62);
            if (lds32(sb + SM_FLAG) != 2 && s_round<7>(sb, p.rec, 0, cta, warp * 7, lane)) sts32(sb + SM_FLAG, 1);
            bar_sync<3, NGW * 32>();
            if (lane == 0) mbar_arrive(sb + B_RFREE);
            gather_role(sb, p, warp, lane);
        }
        finish(sb, sm, p);
    } else {
        if (warp == NW - 1) {
            if (lane == 0) {
                bool ok = true;
#pragma unroll 1
                for (int r = 0; r < NROUND; r++) {
                    if (r == RALT) mbar_wait<100>(sb + B_PFULL + 8 * (NROUND - 1), 0);
                    else if (r >= 1) mbar_wait<100>(sb + B_RFREE + 8 * (r > RALT ? r - 2 : r - 1), 0);
                    ok = ok && wait_round(p.cnt, r);
                    TL(32 + r);
                    fetch_runs(sb, ok, sb + run_buffer(r), p.rec + r * SLAB + (size_t)cta * NB * 256, NB * 256, sb + B_RFULL + 8 * r);
                }
            }
            __syncwarp();
        } else {
            front_end(sb, p, cta, warp - W_F0, lane);
        }
        finish(sb, sm, p);
    }
}

}

extern "C" void kernel_launch(void* const* d_in, const int* in_sizes, int n_in, void* d_out, int out_size) {
    (void)in_sizes; (void)n_in; (void)out_size;
    static const void* tex_ptr = nullptr;
    static cudaTextureObject_t tex = 0;
    static void *rec = nullptr, *cnt = nullptr;
    static CUtensorMap blocks;
    if (tex_ptr != d_in[0]) {
        cudaStreamCaptureMode mode = cudaStreamCaptureModeRelaxed;
        cudaThreadExchangeStreamCaptureMode(&mode);
        cudaFuncSetAttribute(gemnet_kernel, cudaFuncAttributeMaxDynamicSharedMemorySize, SM_TOTAL);
        cudaGetSymbolAddress(&rec, g_rec);
        cudaGetSymbolAddress(&cnt, g_cnt);
        typedef CUresult (*Encode)(CUtensorMap*, CUtensorMapDataType, cuuint32_t, void*, const cuuint64_t*, const cuuint64_t*,
                                   const cuuint32_t*, const cuuint32_t*, CUtensorMapInterleave, CUtensorMapSwizzle,
                                   CUtensorMapL2promotion, CUtensorMapFloatOOBfill);
        void* fn = nullptr;
        cudaDriverEntryPointQueryResult qr;
        cudaGetDriverEntryPoint("cuTensorMapEncodeTiled", &fn, cudaEnableDefault, &qr);
        const cuuint64_t dims[3] = {64, NB, (cuuint64_t)NB * NROUND}, strides[2] = {256, (cuuint64_t)NB * 256};
        const cuuint32_t box[3] = {64, 1, NB}, es[3] = {1, 1, 1};
        ((Encode)fn)(&blocks, CU_TENSOR_MAP_DATA_TYPE_UINT32, 3, rec, dims, strides, box, es, CU_TENSOR_MAP_INTERLEAVE_NONE,
                     CU_TENSOR_MAP_SWIZZLE_NONE, CU_TENSOR_MAP_L2_PROMOTION_NONE, CU_TENSOR_MAP_FLOAT_OOB_FILL_NONE);
        cudaResourceDesc rd = {};
        rd.resType = cudaResourceTypeLinear;
        rd.res.linear.devPtr = d_in[0];
        rd.res.linear.desc = cudaCreateChannelDesc(32, 32, 0, 0, cudaChannelFormatKindUnsigned);
        rd.res.linear.sizeInBytes = (size_t)E_ * 32;
        cudaTextureDesc td = {};
        td.readMode = cudaReadModeElementType;
        cudaCreateTextureObject(&tex, &rd, &td, nullptr);
        cudaThreadExchangeStreamCaptureMode(&mode);
        tex_ptr = d_in[0];
    }
    Params p;
    p.blocks = blocks;
    p.tex = tex;
    p.m = (const uint16_t*)d_in[0];
    p.idx_in = (const int*)d_in[1];
    p.idx_out = (const int*)d_in[2];
    p.dist = (const uint16_t*)d_in[3];
    p.angle = (const uint16_t*)d_in[4];
    p.centers = (const uint16_t*)d_in[5];
    p.ang_freq = (const uint16_t*)d_in[6];
    p.w_rbf = (const uint16_t*)d_in[7];
    p.w_sbf = (const uint16_t*)d_in[8];
    p.w_down = (const uint16_t*)d_in[9];
    p.w_up = (const uint16_t*)d_in[10];
    p.out = (uint16_t*)d_out;
    p.rec = (unsigned char*)rec;
    p.cnt = (unsigned*)cnt;
    gemnet_kernel<<<NB, NTHREADS, SM_TOTAL>>>(p);
}
```

```cpp
#include <cuda.h>
#include <cuda_runtime.h>
#include <cuda_bf16.h>
#include <stdint.h>

namespace {

constexpr int E_ = 160000;
constexpr int T_ = 2560000;
constexpr int NTILE = E_ / 16;
constexpr int NB = 132;
constexpr int TPB = 76;
constexpr int ROWS_PB = TPB * 16;
constexpr int NQUAD = T_ / 4;

constexpr int NGW = 19, NFW = 11;
constexpr int NW = NGW + NFW + 2;
constexpr int W_U1 = 28, W_U2 = 29;
constexpr int TPW = TPB / NGW;
constexpr int NTHREADS = NW * 32;
constexpr int FT = NFW * 32;
constexpr int RPW = NB / NFW;
static_assert(RPW * NFW == NB, "");

constexpr int NROUND = 5, NALL = 4;
#define G_FETCH0 1
#define PFM 1
constexpr int RE = 944, RQ = 1024;
__device__ __forceinline__ constexpr int round_start(int r) {
    return r == 0 ? 0 : r == 1 ? 944 : r == 2 ? 944 + 992 : r == 3 ? 944 + 992 + 960 : r == 4 ? 944 + 992 + 960 + 944 : 4864;
}
static_assert(round_start(NROUND) == (NQUAD / 16 / NB + 1) * 16 && RQ <= 3 * FT, "");

constexpr int BS = 192, BLK = 37, B_BYTE = 148, B_HDR = 188, NOV = 128;
constexpr int CAP2 = 96;
constexpr int TS = CAP2 + 4;
constexpr int TCN = TPB + 32;
constexpr int PCN = NB + 4;
constexpr size_t SLAB = (size_t)NB * NB * BS;

constexpr int TB_ROWS = TPB * TS * 4;
constexpr int TB_SIZE = (TPB * TS * 5 + 127) / 128 * 128;
constexpr int SM_TB = 0;
constexpr int SM_IN0 = SM_TB;
constexpr int SM_PB1 = SM_TB + TB_SIZE;
constexpr int PB_OV = (NB + 2) * BS / 128 * 128;
constexpr int SM_PB = SM_TB + 2 * TB_SIZE;
constexpr int SM_IN = SM_PB + PB_OV + NOV * 8;
constexpr int SM_RUN = SM_IN + RQ * 40;
constexpr int SM_RA = SM_PB;
constexpr int SM_ACC = SM_RA + TPB * 256;
constexpr int SM_ML = SM_ACC + (TPW - 1) * NGW * 1024;
constexpr int SM_PCNT = SM_RUN + 2 * NB * BS;
constexpr int SM_TCNT = SM_PCNT + 2 * PCN * 4;
constexpr int SM_WF = SM_TCNT + 3 * TCN * 4;
constexpr int SM_BAR = SM_WF + 12 * 32 * 4;
constexpr int SM_FLAG = SM_BAR + (7 * NROUND + (TPW - 1) * NGW) * 8;
constexpr int SM_FREQ = SM_FLAG + 4;
constexpr int SM_DEF = SM_FLAG + 16;
constexpr int SM_TOTAL = SM_DEF + NB + 4;
static_assert(RE * 40 <= TB_SIZE && RQ * 40 <= 2 * NB * BS && PB_OV >= (NB + 1) * BS && PB_OV + NOV * 8 <= TB_SIZE &&
              SM_TB + 3 * TB_SIZE <= SM_RUN && SM_RUN % 128 == 0 && SM_BAR % 8 == 0, "layout");
static_assert(SM_ML + NGW * 512 <= SM_PCNT && TPB * 1024 <= SM_PCNT, "epilogue scratch");
static_assert(SM_TOTAL <= 195 * 1024, "stay within the 196 KB carve-out: the gathers need the rest as L1");
constexpr int B_IN = SM_BAR, B_PFULL = B_IN + 8 * NROUND, B_PFREE = B_PFULL + 8 * NROUND, B_RFULL = B_PFREE + 8 * NROUND,
              B_RFREE = B_RFULL + 8 * NROUND, B_TFULL = B_RFREE + 8 * NROUND, B_TFREE = B_TFULL + 8 * NROUND,
              B_DONE = B_TFREE + 8 * NROUND;

__device__ __forceinline__ int stage_buffer(int r) { return r == 0 || r == 3 ? SM_IN0 : r == 2 ? SM_RUN : SM_IN; }
__device__ __forceinline__ int stage_cap(int r) { return r == 0 || r == 3 ? RE : RQ; }
__device__ __forceinline__ int run_buffer(int r) { return SM_RUN + (r & 1) * NB * BS; }

struct Params {
    CUtensorMap blocks;
    cudaTextureObject_t tex;
    const uint16_t *m, *dist, *angle, *centers, *ang_freq, *w_rbf, *w_sbf, *w_down, *w_up;
    const int *idx_in, *idx_out;
    uint16_t* out;
    unsigned char* rec;
    unsigned* cnt;
};

__device__ __align__(256) uint4 g_rec[(NROUND * SLAB + NROUND * NB * NOV * 8) / 16];
__device__ unsigned g_cnt[(NROUND + 1) * 32];

#define TL(slot) do {} while (0)

__device__ __forceinline__ void mbar_init(uint32_t a, uint32_t n) {
    asm volatile("mbarrier.init.shared::cta.b64 [%0], %1;" ::"r"(a), "r"(n) : "memory");
}
__device__ __forceinline__ void mbar_arrive(uint32_t a) {
    asm volatile("mbarrier.arrive.shared::cta.b64 _, [%0];" ::"r"(a) : "memory");
}
template <int SLEEP>
__device__ __forceinline__ void mbar_wait(uint32_t a) {
#pragma unroll 1
    for (int it = 0; it < (1 << 14); it++) {
        uint32_t ok;
        asm volatile("{.reg .pred p; mbarrier.try_wait.parity.shared::cta.b64 p, [%1], 0; selp.u32 %0, 1, 0, p;}"
                     : "=r"(ok) : "r"(a) : "memory");
        if (ok) break;
        __nanosleep(SLEEP);
    }
}
template <int ID, int N> __device__ __forceinline__ void bar_sync() {
    asm volatile("bar.sync %0, %1;" ::"n"(ID), "n"(N) : "memory");
}
__device__ __forceinline__ uint32_t lds32(uint32_t a) {
    uint32_t v; asm volatile("ld.shared.u32 %0, [%1];" : "=r"(v) : "r"(a) : "memory"); return v;
}
__device__ __forceinline__ uint32_t lds8(uint32_t a) {
    uint32_t v; asm volatile("ld.shared.u8 %0, [%1];" : "=r"(v) : "r"(a) : "memory"); return v;
}
__device__ __forceinline__ uint2 lds64(uint32_t a) {
    uint2 v; asm volatile("ld.shared.v2.u32 {%0,%1}, [%2];" : "=r"(v.x), "=r"(v.y) : "r"(a) : "memory"); return v;
}
__device__ __forceinline__ int4 lds128(uint32_t a) {
    int4 v;
    asm volatile("ld.shared.v4.u32 {%0,%1,%2,%3}, [%4];" : "=r"(v.x), "=r"(v.y), "=r"(v.z), "=r"(v.w) : "r"(a) : "memory");
    return v;
}
__device__ __forceinline__ void sts32(uint32_t a, uint32_t v) {
    asm volatile("st.shared.u32 [%0], %1;" ::"r"(a), "r"(v) : "memory");
}
__device__ __forceinline__ void raise_flag(uint32_t sb, uint32_t bit) {
    asm volatile("red.shared.or.b32 [%0], %1;" ::"r"(sb + SM_FLAG), "r"(bit) : "memory");
}
__device__ __forceinline__ uint32_t claim(uint32_t cnt_addr) {
    uint32_t pos;
    asm volatile("atom.shared.add.u32 %0, [%1], 1;" : "=r"(pos) : "r"(cnt_addr) : "memory");
    return pos;
}
__device__ __forceinline__ void put8(bool ok, uint32_t aw, uint32_t w, uint32_t ab, uint32_t b8) {
    asm volatile("{.reg .pred p; setp.ne.u32 p, %0, 0;\n\t"
                 "@p st.shared.u32 [%1], %2; @p st.shared.u8 [%3], %4;}"
                 ::"r"((uint32_t)ok), "r"(aw), "r"(w), "r"(ab), "r"(b8) : "memory");
}
__device__ __forceinline__ uint32_t beq2(uint32_t a, uint32_t b) {
    uint32_t d;
    asm("set.eq.bf16x2.bf16x2 %0, %1, %2;" : "=r"(d) : "r"(a), "r"(b));
    return d;
}
__device__ __forceinline__ uint32_t movm(uint32_t a) {
    uint32_t d;
    asm volatile("movmatrix.sync.aligned.m8n8.trans.b16 %0, %1;" : "=r"(d) : "r"(a));
    return d;
}
__device__ __forceinline__ void mma16816(float (&c)[4], uint32_t a0, uint32_t a1, uint32_t a2, uint32_t a3,
                                         uint32_t b0, uint32_t b1) {
    asm volatile("mma.sync.aligned.m16n8k16.row.col.f32.bf16.bf16.f32 {%0,%1,%2,%3}, {%4,%5,%6,%7}, {%8,%9}, {%0,%1,%2,%3};"
                 : "+f"(c[0]), "+f"(c[1]), "+f"(c[2]), "+f"(c[3])
                 : "r"(a0), "r"(a1), "r"(a2), "r"(a3), "r"(b0), "r"(b1));
}
__device__ __forceinline__ void mma1688(float (&c)[4], uint32_t a0, uint32_t a1, uint32_t b0) {
    asm volatile("mma.sync.aligned.m16n8k8.row.col.f32.bf16.bf16.f32 {%0,%1,%2,%3}, {%4,%5}, {%6}, {%0,%1,%2,%3};"
                 : "+f"(c[0]), "+f"(c[1]), "+f"(c[2]), "+f"(c[3])
                 : "r"(a0), "r"(a1), "r"(b0));
}
__device__ __forceinline__ uint32_t pack_bf16(float lo, float hi) {
    uint32_t d;
    asm("cvt.rn.bf16x2.f32 %0, %1, %2;" : "=r"(d) : "f"(hi), "f"(lo));
    return d;
}
__device__ __forceinline__ float bf_lo(uint32_t v) { return __uint_as_float(v << 16); }
__device__ __forceinline__ float bf_hi(uint32_t v) { return __uint_as_float(v & 0xffff0000u); }
__device__ __forceinline__ float rnd_bf(float x) { return bf_lo(pack_bf16(x, 0.f)); }
__device__ __forceinline__ uint32_t hmul2_bf(uint32_t a, uint32_t b) {
    uint32_t d;
    asm("mul.rn.bf16x2 %0, %1, %2;" : "=r"(d) : "r"(a), "r"(b));
    return d;
}
__device__ __forceinline__ uint32_t hmul2_lo(uint32_t v, uint32_t k) {
    uint32_t d;
    asm("{.reg .b16 l, h; .reg .b32 t; mov.b32 {l, h}, %2; mov.b32 t, {l, l}; mul.rn.bf16x2 %0, %1, t;}"
        : "=r"(d) : "r"(v), "r"(k));
    return d;
}
__device__ __forceinline__ uint32_t hmul2_hi(uint32_t v, uint32_t k) {
    uint32_t d;
    asm("{.reg .b16 l, h; .reg .b32 t; mov.b32 {l, h}, %2; mov.b32 t, {h, h}; mul.rn.bf16x2 %0, %1, t;}"
        : "=r"(d) : "r"(v), "r"(k));
    return d;
}

struct Quad { int4 io, ii; uint2 an; };

__device__ __forceinline__ void stage_inputs(uint32_t sb, const Params& p, int cta, int r) {
    const int qs = cta * (NQUAD / 16) / NB * 16, nq_all = (cta + 1) * (NQUAD / 16) / NB * 16 - qs;
    const int q = qs + round_start(r), n = min(round_start(r + 1), nq_all) - round_start(r);
    const uint32_t dst = sb + stage_buffer(r), cap = stage_cap(r), bar = sb + B_IN + 8 * r;
    uint64_t pol;
    asm volatile("createpolicy.fractional.L2::evict_first.b64 %0, 1.0;" : "=l"(pol));
    asm volatile("mbarrier.arrive.expect_tx.shared::cta.b64 _, [%0], %1;" ::"r"(bar), "r"(n * 40) : "memory");
    auto cp = [&](uint32_t d, const void* src, int bytes) {
        asm volatile("cp.async.bulk.shared::cluster.global.mbarrier::complete_tx::bytes.L2::cache_hint [%0], [%1], %2, [%3], %4;"
                     ::"r"(d), "l"(src), "r"(bytes), "r"(bar), "l"(pol) : "memory");
    };
    cp(dst, p.idx_out + 4 * (size_t)q, n * 16);
    cp(dst + cap * 16, p.idx_in + 4 * (size_t)q, n * 16);
    cp(dst + cap * 32, p.angle + 4 * (size_t)q, n * 8);
}

__device__ __forceinline__ Quad staged_quad(uint32_t in, uint32_t cap, int i) {
    Quad c;
    c.io = lds128(in + i * 16);
    c.ii = lds128(in + cap * 16 + i * 16);
    c.an = lds64(in + cap * 32 + i * 8);
    return c;
}
__device__ __forceinline__ uint32_t cos12(uint32_t x) {
    const uint32_t c = pack_bf16(__cosf(bf_lo(x)), __cosf(bf_hi(x)));
    return (c & 0x80008000u) | ((c << 4) & 0x7FF07FF0u);
}

template <int N, int STEP>
__device__ __forceinline__ void p_quads(uint32_t sb, int r, int i0, uint32_t fr2, bool off = false) {
    const uint32_t pb = sb + (r & 1 ? SM_PB1 : SM_PB), pc = sb + SM_PCNT + (r & 1) * PCN * 4;
    const uint32_t in = sb + stage_buffer(r), cap = stage_cap(r);
    uint32_t x[N][2], val[N][4], bin[N][4], pos[N][4];
#pragma unroll
    for (int n = 0; n < N; n++) {
        Quad v = staged_quad(in, cap, i0 + n * STEP);
        if (off) {
            v.io = make_int4(NB * ROWS_PB, NB * ROWS_PB, NB * ROWS_PB, NB * ROWS_PB);
            v.an = make_uint2(0, 0);
        }
        x[n][0] = hmul2_bf(v.an.x, fr2);
        x[n][1] = hmul2_bf(v.an.y, fr2);
        const bool big = (((x[n][0] & 0x7FFF7FFFu) + 0x3D003D00u) | ((x[n][1] & 0x7FFF7FFFu) + 0x3D003D00u)) & 0x80008000u;
        const uint32_t io[4] = {(uint32_t)v.io.x, (uint32_t)v.io.y, (uint32_t)v.io.z, (uint32_t)v.io.w};
        const uint32_t ii[4] = {(uint32_t)v.ii.x, (uint32_t)v.ii.y, (uint32_t)v.ii.z, (uint32_t)v.ii.w};
#pragma unroll
        for (int i = 0; i < 4; i++) bin[n][i] = __umulhi(io[i], 3532046u);
        asm volatile("atom.shared.add.u32 %0, [%4], %8;\n\tatom.shared.add.u32 %1, [%5], %8;\n\t"
                     "atom.shared.add.u32 %2, [%6], %8;\n\tatom.shared.add.u32 %3, [%7], %8;"
                     : "=&r"(pos[n][0]), "=&r"(pos[n][1]), "=&r"(pos[n][2]), "=&r"(pos[n][3])
                     : "r"(pc + bin[n][0] * 4), "r"(pc + bin[n][1] * 4), "r"(pc + bin[n][2] * 4), "r"(pc + bin[n][3] * 4),
                       "r"(big ? 0x10001u : 1u) : "memory");
#pragma unroll
        for (int i = 0; i < 4; i++) val[n][i] = (ii[i] - bin[n][i]) * ROWS_PB + io[i];
    }
    uint32_t top = 0;
#pragma unroll
    for (int n = 0; n < N; n++) {
#pragma unroll
        for (int h = 0; h < 2; h++) {
            const uint32_t t = cos12(x[n][h]);
#pragma unroll
            for (int i = 2 * h; i < 2 * h + 2; i++) {
                const uint32_t k = pos[n][i], base = pb + bin[n][i] * BS, u = k < 32 ? (bin[n][i] * 6 + k) & 31 : k;
                put8(k < BLK, base + u * 4, (i & 1 ? t & 0xFFFF0000u : t << 16) + (val[n][i] >> 8), base + B_BYTE + u, val[n][i]);
                top = max(top, k);
            }
        }
    }
    if (top < BLK || off) return;
    uint32_t over = 0;
#pragma unroll
    for (int j = 0; j < 4 * N; j++)
        if (pos[j >> 2][j & 3] >= BLK) over |= 1u << j;
    for (; over; over &= over - 1) {
        const int j = __ffs(over) - 1, t = (i0 + (j >> 2) * STEP) * 4 + (j & 3);
        const uint32_t io = lds32(in + t * 4), b = __umulhi(io, 3532046u), k = claim(pc + (NB + 1) * 4);
        uint32_t an;
        asm volatile("ld.shared.u16 %0, [%1];" : "=r"(an) : "r"(in + cap * 32 + t * 2) : "memory");
        if (k < NOV)
            asm volatile("st.shared.v2.u32 [%0], {%1,%2};" ::"r"(pb + PB_OV + k * 8),
                         "r"(cos12(hmul2_bf(an, fr2)) << 16 | lds32(in + cap * 16 + t * 4)),
                         "r"(b << 16 | (io - b * ROWS_PB)) : "memory");
        else
            asm volatile("red.shared.add.u32 [%0], 0x10000;" ::"r"(pc + b * 4) : "memory");
    }
}

__device__ __forceinline__ void publish(unsigned* cnt, int r) {
    asm volatile("red.release.gpu.global.add.u32 [%0], 1;" ::"l"(cnt + r * 32) : "memory");
}
__device__ __forceinline__ bool wait_round(const unsigned* cnt, int r) {
    unsigned c;
    int spins = 0;
    while (true) {
        asm volatile("ld.acquire.gpu.global.u32 %0, [%1];" : "=r"(c) : "l"(cnt + r * 32) : "memory");
        if (c >= NB || ++spins >= (1 << 13)) break;
        __nanosleep(100);
    }
    return c >= NB;
}
__device__ __forceinline__ void fetch_runs(uint32_t sb, bool ok, uint32_t dst, const unsigned char* src, int bytes, uint32_t bar) {
    if (ok) {
        asm volatile("fence.proxy.async.global;" ::: "memory");
        asm volatile("mbarrier.arrive.expect_tx.shared::cta.b64 _, [%0], %1;" ::"r"(bar), "r"(bytes) : "memory");
        uint64_t pol;
        asm volatile("createpolicy.fractional.L2::evict_first.b64 %0, 1.0;" : "=l"(pol));
        asm volatile("cp.async.bulk.shared::cluster.global.mbarrier::complete_tx::bytes.L2::cache_hint [%0], [%1], %2, [%3], %4;"
                     ::"r"(dst), "l"(src), "r"(bytes), "r"(bar), "l"(pol) : "memory");
    } else {
        raise_flag(sb, 2);
        mbar_arrive(bar);
    }
}

struct Sorter {
    uint32_t cb, wb, rb, none;
    uint32_t least = 0xFFFFFFFFu;
    __device__ __forceinline__ Sorter(uint32_t sb, uint32_t buf, int lane) {
        cb = sb + SM_TCNT + buf * TCN * 4;
        wb = sb + SM_TB + buf * TB_SIZE;
        rb = wb + TB_ROWS;
        none = (TPB + lane) << 4;
    }
    __device__ __forceinline__ uint32_t slot(uint32_t loc) const { return claim(cb + (loc >> 4) * 4); }
    __device__ __forceinline__ void store(uint32_t w, uint32_t loc, uint32_t pos) {
        const uint32_t e = (loc >> 4) * TS + pos;
        put8(pos < CAP2, wb + e * 4, w, rb + e, loc & 15);
        least = min(least, pos - CAP2);
    }
    __device__ __forceinline__ void entry(uint2 e, uint32_t bin) {
        if (e.y >> 16 == bin) store(e.x, e.y & 0xFFFFu, slot(e.y & 0xFFFFu));
    }
    static __device__ __forceinline__ void unpack(uint32_t& w, uint32_t& b) {
        const uint32_t v = __byte_perm(w, b, 0x2104) & 0x0FFFFFFFu, idx = __umulhi(v >> 6, 226050911u);
        b = v - idx * ROWS_PB;
        w = (w & 0xFFF00000u) | idx;
    }
    __device__ __forceinline__ bool overflow() const { return least < 0x20000000u; }
};

template <int N>
__device__ __forceinline__ bool s_round(uint32_t sb, const unsigned char* rec, int r, int cta, int p0, int lane) {
    Sorter s(sb, r % 3, lane);
    const uint32_t run = sb + run_buffer(r) + p0 * BS;
    const uint32_t rk = (lane - cta * 6) & 31;
    const uint32_t sub = lane >> 3, k5 = min(lane & 7, 4), tk = (lane & 7) > 4 ? 1000 : 32 + k5;
    const unsigned char* lists = rec + NROUND * SLAB + (size_t)(r * NB + p0) * (NOV * 8);
    const uint32_t hd = lane < N && (NB % N == 0 || p0 + lane < NB) ? lds32(run + lane * BS + B_HDR) : 0u;
    uint32_t more = __ballot_sync(0xffffffffu, (hd & 255) > BLK);
    if (hd & 0x100) s.least = 0;
#pragma unroll
    for (int u0 = 0; u0 < N; u0 += 4) {
        uint32_t w[5], loc[5], pos[5], n[4];
#pragma unroll
        for (int u = 0; u < 4; u++) {
            const bool on = u0 + u < N && (NB % N == 0 || p0 + u0 + u < NB);
            n[u] = on ? lds8(run + (u0 + u) * BS + B_HDR) : 0u;
            if (u0 + u < N) {
                loc[u] = lds8(run + (u0 + u) * BS + B_BYTE + lane);
                w[u] = lds32(run + (u0 + u) * BS + lane * 4);
            }
        }
        w[4] = lds32(run + (u0 + sub) * BS + (32 + k5) * 4);
        loc[4] = lds8(run + (u0 + sub) * BS + B_BYTE + 32 + k5);
#pragma unroll
        for (int u = 0; u < 4; u++) {
            if (u0 + u < N) {
                Sorter::unpack(w[u], loc[u]);
                if (rk >= n[u]) loc[u] = s.none;
                pos[u] = s.slot(loc[u]);
            }
        }
        Sorter::unpack(w[4], loc[4]);
        if (tk >= (sub == 0 ? n[0] : sub == 1 ? n[1] : sub == 2 ? n[2] : n[3])) loc[4] = s.none;
        pos[4] = s.slot(loc[4]);
#pragma unroll
        for (int u = 0; u < 5; u++)
            if (u == 4 || u0 + u < N) s.store(w[u], loc[u], pos[u]);
    }
    if (r == 0) {
        if (lane < N && p0 + lane < NB)
            asm volatile("st.shared.u8 [%0], %1;" ::"r"(sb + SM_DEF + p0 + lane),
                         "r"(more >> lane & 1 ? hd >> 16 : 0u) : "memory");
        return s.overflow();
    }
    if (r == 1) more |= __ballot_sync(0xffffffffu, lane < N && lds8(sb + SM_DEF + p0 + lane)) << 16;
    for (; more; more &= more - 1) {
        const int u = __ffs(more) - 1;
        const uint32_t n = u < 16 ? lds32(run + u * BS + B_HDR) >> 16 : lds8(sb + SM_DEF + p0 + u - 16);
        const unsigned char* list = lists + (u < 16 ? u : u - 16 - NB) * (NOV * 8);
        uint2 e[NOV / 32];
#pragma unroll
        for (int i = 0; i < NOV / 32; i++) {
            e[i].y = 0xFFFF0000u;
            if (i * 32 + lane < n)
                asm volatile("ld.relaxed.gpu.global.v2.u32 {%0,%1}, [%2];" : "=r"(e[i].x), "=r"(e[i].y)
                             : "l"(list + (i * 32 + lane) * 8) : "memory");
        }
#pragma unroll
        for (int i = 0; i < NOV / 32; i++) s.entry(e[i], cta);
    }
    return s.overflow();
}

__device__ __forceinline__ uint2 rbf_tile(int tile, int lane, const Params& p) {
    const int r0 = tile * 16 + (lane >> 2);
    const uint32_t d0 = __ldg(p.dist + r0) * 0x10001u, d1 = __ldg(p.dist + r0 + 8) * 0x10001u;
    const uint32_t cc = __ldg(reinterpret_cast<const uint32_t*>(p.centers) + (lane & 3));
    auto rbf = [&](uint32_t d) {
        uint32_t t;
        asm("sub.rn.bf16x2 %0, %1, %2;" : "=r"(t) : "r"(d), "r"(cc));
        t = hmul2_bf(hmul2_bf(t, t), 0xC120C120u);
        return pack_bf16(__expf(bf_lo(t)), __expf(bf_hi(t)));
    };
    return make_uint2(rbf(d0), rbf(d1));
}

struct Weights {
    uint32_t v[12];
    __device__ __forceinline__ Weights(uint32_t sb, int lane) {
#pragma unroll
        for (int i = 0; i < 12; i++) v[i] = lds32(sb + SM_WF + i * 128 + lane * 4);
    }
};
struct MRows {
    uint2 a, b;
    __device__ __forceinline__ MRows(int4 v) : a(make_uint2(v.x, v.y)), b(make_uint2(v.z, v.w)) {}
    __device__ __forceinline__ MRows(int tile, int lane, const Params& p) {
        const uint2* m2 = reinterpret_cast<const uint2*>(p.m) + (tile * 16 + (lane >> 2)) * 4 + (lane & 3);
        a = __ldg(m2);
        b = __ldg(m2 + 32);
    }
};

__device__ __forceinline__ void epilogue(const float (&s0)[4], const float (&s1)[4], uint2 ra, const MRows& mr,
                                         const Weights& w, int tile, int lane, uint16_t* out) {
    uint32_t h[4], l[4];
    h[0] = pack_bf16(s0[0], s0[1]); h[1] = pack_bf16(s0[2], s0[3]);
    h[2] = pack_bf16(s1[0], s1[1]); h[3] = pack_bf16(s1[2], s1[3]);
    l[0] = pack_bf16(s0[0] - bf_lo(h[0]), s0[1] - bf_hi(h[0]));
    l[1] = pack_bf16(s0[2] - bf_lo(h[1]), s0[3] - bf_hi(h[1]));
    l[2] = pack_bf16(s1[0] - bf_lo(h[2]), s1[1] - bf_hi(h[2]));
    l[3] = pack_bf16(s1[2] - bf_lo(h[3]), s1[3] - bf_hi(h[3]));
    uint32_t a[4];
#pragma unroll
    for (int n = 0; n < 2; n++) {
        float y[4] = {}, gs[4] = {};
        mma16816(y, l[0], l[1], l[2], l[3], w.v[2 * n], w.v[2 * n + 1]);
        mma16816(y, h[0], h[1], h[2], h[3], w.v[2 * n], w.v[2 * n + 1]);
        mma1688(gs, ra.x, ra.y, w.v[8 + n]);
        a[2 * n] = pack_bf16(y[0] * gs[0], y[1] * gs[1]);
        a[2 * n + 1] = pack_bf16(y[2] * gs[2], y[3] * gs[3]);
    }
    const uint32_t mm[4] = {mr.a.x, mr.b.x, mr.a.y, mr.b.y};
    uint32_t o[4];
#pragma unroll
    for (int n = 0; n < 2; n++) {
        float u[4] = {}, hr[4] = {};
        mma16816(u, a[0], a[1], a[2], a[3], w.v[4 + 2 * n], w.v[5 + 2 * n]);
        mma1688(hr, ra.x, ra.y, w.v[10 + n]);
#pragma unroll
        for (int k = 0; k < 2; k++) {
            const uint32_t t = hmul2_bf(pack_bf16(u[2 * k], u[2 * k + 1]), pack_bf16(hr[2 * k], hr[2 * k + 1]));
            asm("add.rn.bf16x2 %0, %1, %2;" : "=r"(o[2 * n + k]) : "r"(mm[2 * n + k]), "r"(t));
        }
    }
    uint2* out2 = reinterpret_cast<uint2*>(out) + (tile * 16 + (lane >> 2)) * 4 + (lane & 3);
    out2[0] = make_uint2(o[0], o[2]);
    out2[32] = make_uint2(o[1], o[3]);
}

__device__ __forceinline__ void load_acc(uint32_t base, int lt, int lane, float (&s0)[4], float (&s1)[4]) {
#pragma unroll
    for (int i = 0; i < 4; i++) {
        s0[i] = __uint_as_float(lds32(base + lt * 1024 + i * 128 + lane * 4));
        s1[i] = __uint_as_float(lds32(base + lt * 1024 + (4 + i) * 128 + lane * 4));
    }
}

__device__ __forceinline__ uint32_t and_or(uint32_t a, uint32_t m, uint32_t c) {
    uint32_t d;
    asm("lop3.b32 %0, %1, %2, %3, 0xEA;" : "=r"(d) : "r"(a), "r"(m), "r"(c));
    return d;
}

struct Group {
    uint2 v0, v1;
    uint32_t k, rows;
    __device__ __forceinline__ void issue(uint3 e, cudaTextureObject_t tex, uint32_t q) {
        v0 = tex1Dfetch<uint2>(tex, (int)and_or(e.x << 2, 0xFFFFCu, q));
        v1 = tex1Dfetch<uint2>(tex, (int)and_or(e.y << 2, 0xFFFFCu, q));
        k = __byte_perm(e.x, e.y, 0x7632);
        rows = e.z;
    }
    static __device__ __forceinline__ uint3 entries(uint32_t aw, uint32_t ar) {
        uint3 e;
        asm volatile("ld.volatile.shared.v2.u32 {%0,%1}, [%2];" : "=r"(e.x), "=r"(e.y) : "r"(aw) : "memory");
        asm volatile("ld.volatile.shared.u32 %0, [%1];" : "=r"(e.z) : "r"(ar) : "memory");
        return e;
    }
    __device__ __forceinline__ void consume(float (&c0)[4], float (&c1)[4], uint32_t gg, uint32_t gg8, uint32_t bias) const {
        const uint32_t ra = __byte_perm(rows, 0, 0x2404), rc = __byte_perm(rows, 0, 0x3414);
        const uint32_t a0 = beq2(ra, gg), a1 = beq2(ra, gg8);
        const uint32_t a2 = beq2(rc, gg), a3 = beq2(rc, gg8);
        const uint32_t c = and_or(k, 0x80008000u, and_or(k >> 4, 0x07FF07FFu, bias));
        const uint32_t b0 = movm(hmul2_lo(v0.x, c)), b1 = movm(hmul2_hi(v1.x, c));
        const uint32_t b2 = movm(hmul2_lo(v0.y, c)), b3 = movm(hmul2_hi(v1.y, c));
        mma16816(c0, a0, a1, a2, a3, b0, b1);
        mma16816(c1, a0, a1, a2, a3, b2, b3);
    }
};

constexpr int GD = 2;

__device__ __forceinline__ void slow_path(uint32_t sb, float* acc, const Params& p) {
    const int tid = threadIdx.x;
    for (int i = tid; i < TPB * 256; i += NTHREADS) acc[i] = 0.f;
    __syncthreads();
    const uint32_t fr2 = lds32(sb + SM_FREQ);
    for (int t = tid; t < T_; t += NTHREADS) {
        const uint32_t lo = (uint32_t)(p.idx_out[t] - (int)blockIdx.x * ROWS_PB);
        if (lo < (uint32_t)ROWS_PB) {
            const float c = rnd_bf(cosf(bf_lo(hmul2_bf(p.angle[t], fr2))));
            const uint32_t* row = reinterpret_cast<const uint32_t*>(p.m) + (size_t)p.idx_in[t] * 8;
            float* a = acc + (lo >> 4) * 256 + (lo & 8) * 8 + (lo & 7) * 4;
#pragma unroll
            for (int i = 0; i < 8; i++) {
                const uint32_t x = row[i];
                atomicAdd(a + (i & 1) * 128 + (i >> 1), c * bf_lo(x));
                atomicAdd(a + (i & 1) * 128 + (i >> 1) + 32, c * bf_hi(x));
            }
        }
    }
    __syncthreads();
    for (int lt = tid >> 5; lt < TPB && blockIdx.x * TPB + lt < NTILE; lt += NW) {
        const int tile = blockIdx.x * TPB + lt, lane = tid & 31;
        float s0[4], s1[4];
        load_acc(sb, lt, lane, s0, s1);
        epilogue(s0, s1, rbf_tile(tile, lane, p), MRows(tile, lane, p), Weights(sb, lane), tile, lane, p.out);
    }
}

__device__ __forceinline__ void prefetch_m(const Params& p, int cta) {
    const int l0 = cta * (E_ / 4) / NB, l1 = (cta + 1) * (E_ / 4) / NB;
    asm volatile("cp.async.bulk.prefetch.L2.global [%0], %1;" ::"l"(p.m + (size_t)l0 * 64), "r"((l1 - l0) * 128) : "memory");
}

__device__ __forceinline__ void front_end(uint32_t sb, const Params& p, int cta, int fw, int lane) {
    const int ft = fw * 32 + lane;
    const int nq_all = (cta + 1) * (NQUAD / 16) / NB * 16 - cta * (NQUAD / 16) / NB * 16;
    for (int k = fw; k < 12; k += NFW) {
        const int g = lane >> 2, q = lane & 3;
        const int n = k < 8 ? (k >> 1) & 1 : k & 1;
        const int row = k < 8 ? 4 * q + 2 * (k & 1) : 2 * q;
        const uint16_t* w = (k < 4 ? p.w_down : k < 8 ? p.w_up : k < 10 ? p.w_sbf : p.w_rbf) +
                            row * 16 + 4 * (g >> 1) + 2 * n + (g & 1);
        sts32(sb + SM_WF + (k * 32 + lane) * 4, (uint32_t)w[0] | ((uint32_t)w[16] << 16));
    }
    const uint32_t fr2 = lds32(sb + SM_FREQ);
    {
        constexpr int r = NROUND - 1;
        static_assert(NALL == r, "");
        const int nq = nq_all - round_start(r);
        mbar_wait<20>(sb + B_PFREE + 8 * (r - 2));
        mbar_wait<20>(sb + B_IN + 8 * r);
        if (fw == 1) TL(3 + r);
        if (PFM == 1 && ft == 0) prefetch_m(p, cta);
        p_quads<2, FT>(sb, r, ft, fr2);
        if (2 * FT + fw * 32 < nq) p_quads<1, 0>(sb, r, 2 * FT + ft, fr2, 2 * FT + ft >= nq);
        asm volatile("fence.proxy.async.shared::cta;" ::: "memory");
        __syncwarp();
        if (lane == 0) mbar_arrive(sb + B_PFULL + 8 * r);
        if (fw == 1) TL(24 + r);
        if (PFM == 2 && ft == 0) prefetch_m(p, cta);
    }
    mbar_wait<50>(sb + B_RFREE);
#pragma unroll 1
    for (int r = 1; r < NROUND; r++) {
        mbar_wait<50>(sb + (r < 3 ? B_PFREE + 8 * (r + 2) : B_TFREE + 8 * (r - 3)));
        mbar_wait<50>(sb + B_RFULL + 8 * r);
        if (fw == 1) TL(56 + r);
        if (!(lds32(sb + SM_FLAG) & 2) && s_round<RPW>(sb, p.rec, r, cta, fw * RPW, lane)) raise_flag(sb, 1);
        __syncwarp();
        if (lane == 0) {
            mbar_arrive(sb + B_TFULL + 8 * r);
            mbar_arrive(sb + B_RFREE + 8 * r);
        }
        if (fw == 1) TL(40 + r);
    }
    bar_sync<2, FT>();
    if (lds32(sb + SM_FLAG) != 0) return;
    mbar_wait<100>(sb + B_TFREE + 8 * 2);
#pragma unroll 1
    for (int k0 = 0; k0 < 8; k0 += 4) {
#pragma unroll
        for (int k = k0; k < k0 + 4; k++) {
            const int lt = min(fw + k * NFW, min(TPB, NTILE - cta * TPB) - 1);
            const uint2 ra = rbf_tile(cta * TPB + lt, lane, p);
            asm volatile("st.shared.v2.u32 [%0], {%1,%2};" ::"r"(sb + SM_RA + lt * 256 + lane * 8), "r"(ra.x), "r"(ra.y) : "memory");
        }
    }
#pragma unroll
    for (int k = 0; k < 2; k++) {
        const int gw = fw + k * NFW;
        if (gw < NGW && cta * TPB + (TPW - 1) * NGW + gw < NTILE) {
            const MRows mr(cta * TPB + (TPW - 1) * NGW + gw, lane, p);
            asm volatile("st.shared.v4.u32 [%0], {%1,%2,%3,%4};" ::"r"(sb + SM_ML + gw * 512 + lane * 16),
                         "r"(mr.a.x), "r"(mr.a.y), "r"(mr.b.x), "r"(mr.b.y) : "memory");
        }
    }
    __syncwarp();
    if (lane == 0) mbar_arrive(sb + B_TFULL);
    mbar_wait<50>(sb + B_TFULL);
    const Weights w(sb, lane);
#pragma unroll 1
    for (int lt = fw; lt < (TPW - 1) * NGW && cta * TPB + lt < NTILE; lt += NFW) {
        const int tile = cta * TPB + lt;
        const MRows mr(tile, lane, p);
        const uint2 ra = lds64(sb + SM_RA + lt * 256 + lane * 8);
        mbar_wait<50>(sb + B_DONE + 8 * lt);
        float s0[4], s1[4];
        load_acc(sb + SM_ACC, lt, lane, s0, s1);
        epilogue(s0, s1, ra, mr, w, tile, lane, p.out);
    }
}

__device__ __forceinline__ void gather_role(uint32_t sb, const Params& p, int warp, int lane) {
    const int g = lane >> 2, q = lane & 3;
    const cudaTextureObject_t tex = p.tex;
    float acc[TPW][2][4];
#pragma unroll
    for (int j = 0; j < TPW; j++)
#pragma unroll
        for (int n = 0; n < 2; n++)
#pragma unroll
            for (int i = 0; i < 4; i++) acc[j][n][i] = 0.f;
    const uint32_t gg = g * 0x01000100u, gg8 = gg + 0x08000800u;
    uint32_t qo = q, bias = 0x38003800u;
    asm volatile("" : "+r"(qo), "+r"(bias));
    static_assert(TPW == 4, "eight lanes per tile");
#pragma unroll 1
    for (int r = 0; r < NROUND; r++) {
        const int buf = r % 3;
        if (r > 0) mbar_wait<200>(sb + B_TFULL + 8 * r);
        if (warp == 0) TL(10 + r);
        const uint32_t tb = sb + SM_TB + buf * TB_SIZE;
        const uint32_t aw = tb + warp * (TS * 4) + g * 8, ar = tb + TB_ROWS + warp * TS + q * 4;
        const uint32_t sj = warp + (lane >> 3) * NGW;
        const uint32_t cj = sb + SM_TCNT + (sj + buf * TCN) * 4;
        const uint32_t n = min(lds32(cj), (uint32_t)CAP2), np = (n + 15) & ~15u;
        const uint32_t e = n + (lane & 7);
        if (e < np) sts32(tb + (sj * TS + e) * 4, 0x3FFFFu);
        if (e + 8 < np) sts32(tb + (sj * TS + e + 8) * 4, 0x3FFFFu);
        __syncwarp();
        if ((lane & 7) == 0) sts32(cj, 0);
        const uint32_t act = __reduce_add_sync(0xffffffffu, (lane & 7) == 0 ? ((1u << (np >> 4)) - 1) << lane : 0u);
        const bool hand = r == NROUND - 1 && lds32(sb + SM_FLAG) == 0;
        if (hand) mbar_wait<50>(sb + B_TFREE + 8 * 2);
        auto hand_over = [&](int j, const float (&c)[2][4]) {
            const uint32_t d = sb + SM_ACC + (j * NGW + warp) * 1024 + lane * 4;
#pragma unroll
            for (int i = 0; i < 8; i++) sts32(d + i * 128, __float_as_uint(c[i >> 2][i & 3]));
            __syncwarp();
            if (lane == 0) mbar_arrive(sb + B_DONE + 8 * (j * NGW + warp));
        };
        Group x[GD];
        if (act & 0xF0F0F0F0u) {
#pragma unroll
            for (int j = 0; j < TPW; j++) {
#pragma unroll 1
                for (int k = 4; act >> (8 * j + k) & 1; k++) {
                    const int o = j * NGW * TS + k * 16;
                    x[0].issue(Group::entries(aw + o * 4, ar + o), tex, qo);
                    x[0].consume(acc[j][0], acc[j][1], gg, gg8, bias);
                }
            }
        }
#pragma unroll
        for (int s = -GD; s < 4 * TPW; s++) {
            const int t = s + GD, o = (t >> 2) * NGW * TS + (t & 3) * 16;
            uint3 e;
            if (t < 4 * TPW) e = Group::entries(aw + o * 4, ar + o);
            if (s >= 0 && (act >> (8 * (s >> 2) + (s & 3)) & 1)) x[s % GD].consume(acc[s >> 2][0], acc[s >> 2][1], gg, gg8, bias);
            if (t < 4 * TPW) x[t % GD].issue(e, tex, (act >> (8 * (t >> 2) + (t & 3)) & 1) ? qo : 0x400000u);
            if (s >= 0 && (s & 3) == 3 && s < 4 * (TPW - 1) && hand) hand_over(s >> 2, acc[s >> 2]);
        }
        __syncwarp();
        if (lane == 0) mbar_arrive(sb + B_TFREE + 8 * r);
        if (warp == 0) TL(17 + r);
    }
    const int tile = blockIdx.x * TPB + (TPW - 1) * NGW + warp;
    if (lds32(sb + SM_FLAG) == 0 && tile < NTILE) {
        mbar_wait<50>(sb + B_TFULL);
        const MRows mr(lds128(sb + SM_ML + warp * 512 + lane * 16));
        epilogue(acc[TPW - 1][0], acc[TPW - 1][1], lds64(sb + SM_RA + ((TPW - 1) * NGW + warp) * 256 + lane * 8), mr,
                 Weights(sb, lane), tile, lane, p.out);
    }
}

__device__ __forceinline__ void flush_round(uint32_t sb, const Params& p, int cta, int r, int lane) {
    const uint32_t pb = sb + (r & 1 ? SM_PB1 : SM_PB), pc = sb + SM_PCNT + (r & 1) * PCN * 4;
    mbar_wait<20>(sb + B_PFULL + 8 * r);
    const uint32_t nov = min(lds32(pc + (NB + 1) * 4), (uint32_t)NOV);
#pragma unroll
    for (int b = lane; b < NB; b += 32) {
        const uint32_t n = lds32(pc + b * 4);
        sts32(pb + b * BS + B_HDR, (n > BLK + NOV ? 0x100u : n) | nov << 16);
        sts32(pc + b * 4, 0);
    }
    __syncwarp();
    if (lane == 0) sts32(pc + (NB + 1) * 4, 0);
    asm volatile("fence.proxy.async.shared::cta;" ::: "memory");
    __syncwarp();
    if (lane == 0) {
        asm volatile("cp.async.bulk.tensor.3d.global.shared::cta.tile.bulk_group [%0, {%1, %2, %3}], [%4];"
                     ::"l"(&p.blocks), "r"(0), "r"(cta), "r"(r * NB), "r"(pb) : "memory");
        if (nov)
            asm volatile("cp.async.bulk.global.shared::cta.bulk_group [%0], [%1], %2;"
                         ::"l"(p.rec + NROUND * SLAB + (size_t)(r * NB + cta) * (NOV * 8)), "r"(pb + PB_OV),
                           "r"((nov * 8 + 31) & ~31u) : "memory");
        asm volatile("cp.async.bulk.commit_group;" ::: "memory");
        if (r < 2) stage_inputs(sb, p, cta, r + 3);
    }
}

__global__ void __launch_bounds__(NTHREADS, 1) gemnet_kernel(const __grid_constant__ Params p) {
    extern __shared__ __align__(128) unsigned char sm[];
    const uint32_t sb = (uint32_t)__cvta_generic_to_shared(sm);
    const int tid = threadIdx.x, warp = tid >> 5, lane = tid & 31;
    const int cta = blockIdx.x;

    if (tid == 0) {
        mbar_init(sb + B_IN, 1);
        asm volatile("fence.mbarrier_init.release.cluster;" ::: "memory");
        stage_inputs(sb, p, cta, 0);
    } else if (tid == 32) {
        sts32(sb + SM_FREQ, (uint32_t)__ldg(p.ang_freq) * 0x10001u);
        sts32(sb + SM_FLAG, 0);
    } else if (tid >= 96 && tid < 96 + NROUND) {
        const int r = tid - 96;
        mbar_init(sb + B_PFULL + 8 * r, r == 1 ? NW - 1 : r < NALL ? NW - 2 : NFW);
        mbar_init(sb + B_PFREE + 8 * r, 1);
        mbar_init(sb + B_RFULL + 8 * r, 1);
        mbar_init(sb + B_TFULL + 8 * r, NFW);
        mbar_init(sb + B_TFREE + 8 * r, NGW);
        if (r >= 1) mbar_init(sb + B_IN + 8 * r, 1);
        mbar_init(sb + B_RFREE + 8 * r, r == 0 ? NGW : NFW);
        asm volatile("fence.mbarrier_init.release.cluster;" ::: "memory");
    }
    if (tid >= 896 && tid < 896 + (TPW - 1) * NGW) mbar_init(sb + B_DONE + 8 * (tid - 896), 1);
    if (tid >= 512 && tid < 512 + 2 * PCN) sts32(sb + SM_PCNT + (tid - 512) * 4, 0);
    if (tid < 3 * TCN) sts32(sb + SM_TCNT + tid * 4, tid % TCN < TPB ? 0u : 0x40000000u);
    __syncthreads();
    if (warp == 0) TL(3);

    if (warp != W_U1) {
        const int pt = warp < W_U1 ? tid : warp == W_U2 ? (NW - 2) * 32 + lane : tid - 64;
        const uint32_t fr2 = lds32(sb + SM_FREQ);
#pragma unroll
        for (int r = 0; r < NALL; r++) {
            if (warp == W_U2 && r != 1) continue;
            if (r >= 2) mbar_wait<20>(sb + B_PFREE + 8 * (r - 2));
            mbar_wait<20>(sb + B_IN + 8 * r);
            if (warp == 0) TL(3 + r + (r == 0 ? 20 : 0));
            constexpr int FULL = (NW - 2) * 32;
            p_quads<1, 0>(sb, r, pt, fr2, round_start(r + 1) - round_start(r) < FULL && pt >= round_start(r + 1) - round_start(r));
            asm volatile("fence.proxy.async.shared::cta;" ::: "memory");
            __syncwarp();
            if (lane == 0) mbar_arrive(sb + B_PFULL + 8 * r);
            if (warp == 0) TL(24 + r);
        }
    }

    if (warp < NGW) {
        if (G_FETCH0 && tid == 0) {
            mbar_wait<20>(sb + B_PFULL + 8 * 2);
            const bool ok = wait_round(p.cnt, 0);
            TL(32);
            fetch_runs(sb, ok, sb + run_buffer(0), p.rec + (size_t)cta * NB * BS, NB * BS, sb + B_RFULL);
        }
        __syncwarp();
        mbar_wait<50>(sb + B_RFULL);
        mbar_wait<50>(sb + B_PFULL + 8 * 3);
        if (warp == 0) TL(62);
        if (!(lds32(sb + SM_FLAG) & 2) && s_round<7>(sb, p.rec, 0, cta, warp * 7, lane)) raise_flag(sb, 1);
        bar_sync<3, NGW * 32>();
        if (lane == 0) mbar_arrive(sb + B_RFREE);
        gather_role(sb, p, warp, lane);
    } else if (warp == W_U1) {
        if (lane == 0) {
            stage_inputs(sb, p, cta, 1);
            stage_inputs(sb, p, cta, 2);
        }
#pragma unroll 1
        for (int r = 0; r < NROUND; r += r == 0 ? 2 : 1) {
            __syncwarp();
            flush_round(sb, p, cta, r, lane);
            if (lane == 0) {
                asm volatile("cp.async.bulk.wait_group.read 0;" ::: "memory");
                mbar_arrive(sb + B_PFREE + 8 * r);
                asm volatile("cp.async.bulk.wait_group 0;" ::: "memory");
                publish(p.cnt, r);
                TL(48 + r);
            }
        }
        __syncwarp();
    } else if (warp == W_U2) {
        flush_round(sb, p, cta, 1, lane);
        if (lane == 0) {
            asm volatile("cp.async.bulk.wait_group.read 0;" ::: "memory");
            mbar_arrive(sb + B_PFREE + 8);
            asm volatile("cp.async.bulk.wait_group 0;" ::: "memory");
            publish(p.cnt, 1);
            TL(49);
            bool ok = true;
#pragma unroll 1
            for (int r = G_FETCH0; r < NROUND; r++) {
                mbar_wait<100>(sb + (r >= 2 ? B_RFREE + 8 * (r - 2) : B_PFULL + 8 * 2));
                ok = ok && wait_round(p.cnt, r);
                TL(32 + r);
                fetch_runs(sb, ok, sb + run_buffer(r), p.rec + r * SLAB + (size_t)cta * NB * BS, NB * BS, sb + B_RFULL + 8 * r);
            }
        }
        __syncwarp();
    } else {
        front_end(sb, p, cta, warp < W_U1 ? warp - NGW : warp - NGW - 2, lane);
    }
    __syncthreads();
    if (lds32(sb + SM_FLAG) != 0) slow_path(sb, reinterpret_cast<float*>(sm), p);
    if (tid == 0) {
        TL(1);
        if (atomicAdd(p.cnt + NROUND * 32, 1u) == NB - 1)
            for (int r = 0; r <= NROUND; r++) p.cnt[r * 32] = 0;
    }
}

}

extern "C" void kernel_launch(void* const* d_in, const int* in_sizes, int n_in, void* d_out, int out_size) {
    (void)in_sizes; (void)n_in; (void)out_size;
    static const void* tex_ptr = nullptr;
    static cudaTextureObject_t tex = 0;
    static void *rec = nullptr, *cnt = nullptr;
    static CUtensorMap blocks;
    if (tex_ptr != d_in[0]) {
        cudaStreamCaptureMode mode = cudaStreamCaptureModeRelaxed;
        cudaThreadExchangeStreamCaptureMode(&mode);
        cudaFuncSetAttribute(gemnet_kernel, cudaFuncAttributeMaxDynamicSharedMemorySize, SM_TOTAL);
        cudaGetSymbolAddress(&rec, g_rec);
        cudaGetSymbolAddress(&cnt, g_cnt);
        typedef CUresult (*Encode)(CUtensorMap*, CUtensorMapDataType, cuuint32_t, void*, const cuuint64_t*, const cuuint64_t*,
                                   const cuuint32_t*, const cuuint32_t*, CUtensorMapInterleave, CUtensorMapSwizzle,
                                   CUtensorMapL2promotion, CUtensorMapFloatOOBfill);
        void* fn = nullptr;
        cudaDriverEntryPointQueryResult qr;
        cudaGetDriverEntryPoint("cuTensorMapEncodeTiled", &fn, cudaEnableDefault, &qr);
        const cuuint64_t dims[3] = {BS / 4, NB, (cuuint64_t)NB * NROUND}, strides[2] = {BS, (cuuint64_t)NB * BS};
        const cuuint32_t box[3] = {BS / 4, 1, NB}, es[3] = {1, 1, 1};
        ((Encode)fn)(&blocks, CU_TENSOR_MAP_DATA_TYPE_UINT32, 3, rec, dims, strides, box, es, CU_TENSOR_MAP_INTERLEAVE_NONE,
                     CU_TENSOR_MAP_SWIZZLE_NONE, CU_TENSOR_MAP_L2_PROMOTION_NONE, CU_TENSOR_MAP_FLOAT_OOB_FILL_NONE);
        cudaResourceDesc rd = {};
        rd.resType = cudaResourceTypeLinear;
        rd.res.linear.devPtr = d_in[0];
        rd.res.linear.desc = cudaCreateChannelDesc(32, 32, 0, 0, cudaChannelFormatKindUnsigned);
        rd.res.linear.sizeInBytes = (size_t)E_ * 32;
        cudaTextureDesc td = {};
        td.readMode = cudaReadModeElementType;
        cudaCreateTextureObject(&tex, &rd, &td, nullptr);
        cudaThreadExchangeStreamCaptureMode(&mode);
        tex_ptr = d_in[0];
    }
    Params p;
    p.blocks = blocks;
    p.tex = tex;
    p.m = (const uint16_t*)d_in[0];
    p.idx_in = (const int*)d_in[1];
    p.idx_out = (const int*)d_in[2];
    p.dist = (const uint16_t*)d_in[3];
    p.angle = (const uint16_t*)d_in[4];
    p.centers = (const uint16_t*)d_in[5];
    p.ang_freq = (const uint16_t*)d_in[6];
    p.w_rbf = (const uint16_t*)d_in[7];
    p.w_sbf = (const uint16_t*)d_in[8];
    p.w_down = (const uint16_t*)d_in[9];
    p.w_up = (const uint16_t*)d_in[10];
    p.out = (uint16_t*)d_out;
    p.rec = (unsigned char*)rec;
    p.cnt = (unsigned*)cnt;
    gemnet_kernel<<<NB, NTHREADS, SM_TOTAL>>>(p);
}
```
